```python
import torch

def _softmax(x, axis=-1):
    return torch.softmax(x, dim=axis)
def _gelu(x):
    return torch.nn.functional.gelu(x, approximate="tanh")
def _silu(x):
    return torch.nn.functional.silu(x)
def _sigmoid(x):
    return torch.sigmoid(x)
def _layernorm(x, axis=-1, eps=1e-5):
    m = x.mean(dim=axis, keepdim=True)
    v = x.var(dim=axis, keepdim=True, unbiased=False)
    return (x - m) / torch.sqrt(v + eps)
def _scatter_add(tgt, idx, src, axis=0):
    return tgt.clone().index_add_(axis, idx, src)
def _segment_sum(src, seg, n):
    out = torch.zeros((n,) + src.shape[1:], dtype=src.dtype)
    return out.index_add_(0, seg, src)
def _pad(x, pw):
    flat = tuple(v for pair in reversed(pw) for v in pair)
    return torch.nn.functional.pad(x, flat)

kernel_name = 'gated_mix__sliding_block_cached__glu_gated_bilinear__decode'

def setup_inputs():

    _w = (lambda a: (lambda t: t.to(torch.bfloat16) if t.is_floating_point() else t)(torch.as_tensor(a)))
    def _A_setup():
        B, Sq, D = 2, 1, 512
        Hq, Hkv, Sk, Dh = 32, 32, 4096, 128
        assert Hq % Hkv == 0, (Hq, Hkv)
        return {
            "x": _w((lambda *s: torch.randn(*s, dtype=torch.bfloat16) * 0.05)(B, Sq, D)),
            "k_cache": _w((lambda *s: torch.randn(*s, dtype=torch.bfloat16) * 6.4)(B, Hkv, Sk, Dh)),
            "v_cache": _w((lambda *s: torch.randn(*s, dtype=torch.bfloat16) * 0.05)(B, Hkv, Sk, Dh)),
            "wq": _w((lambda *s: torch.randn(*s, dtype=torch.bfloat16) * 6.4)(D, Hq * Dh) * (D ** -0.5)),
            "wo": _w((lambda *s: torch.randn(*s, dtype=torch.bfloat16) * 0.05)(Hq * Dh, D) * ((Hq * Dh) ** -0.5)),
        }
    _A_in = _A_setup()

    def _B_setup():
        B, S, D, F = 2, 1, 512, 1376
        return {
            "x": _w((lambda *s: torch.randn(*s, dtype=torch.bfloat16) * 0.05)(B, S, D)),
            "w_gate": _w((lambda *s: torch.randn(*s, dtype=torch.bfloat16) * 0.4)(D, F) * (D ** -0.5)),
            "w_up": _w((lambda *s: torch.randn(*s, dtype=torch.bfloat16) * 0.4)(D, F) * (D ** -0.5)),
            "w_down": _w((lambda *s: torch.randn(*s, dtype=torch.bfloat16) * 0.4)(F, D) * (F ** -0.5)),
        }
    _B_in = _B_setup()

    return {
        "A_x": _A_in["x"],
        "A_k_cache": _A_in["k_cache"],
        "A_v_cache": _A_in["v_cache"],
        "A_wq": _A_in["wq"],
        "A_wo": _A_in["wo"],
        "B_x": _B_in["x"],
        "B_w_gate": _B_in["w_gate"],
        "B_w_up": _B_in["w_up"],
        "B_w_down": _B_in["w_down"],
        "gate_w": _w((lambda *s: torch.randn(*s, dtype=torch.bfloat16) * 0.05)(512) * 16.0),
    }

def reference(A_x, A_k_cache, A_v_cache, A_wq, A_wo, B_x, B_w_gate, B_w_up, B_w_down, gate_w):
    def _A_ref(x, k_cache, v_cache, wq, wo):
        B, Sq, D = x.shape
        Hq, Dh = 32, 128
        Hkv, Sk = k_cache.shape[1], k_cache.shape[2]
        W = min(4096, max(256, Sk // 4))
        rep = Hq // Hkv
        q = (lambda x, *d: x.permute(*d))((x @ wq).reshape(B, Sq, Hq, Dh), 0, 2, 1, 3)
        k = (lambda x, n, axis: torch.repeat_interleave(x, n, dim=axis))(k_cache[:, :, Sk - W:, :], rep, axis=1)
        v = (lambda x, n, axis: torch.repeat_interleave(x, n, dim=axis))(v_cache[:, :, Sk - W:, :], rep, axis=1)
        scores = torch.einsum("bhqd,bhkd->bhqk", q, k) * (Dh ** -0.5)
        p = _softmax(scores, axis=-1)
        o = torch.einsum("bhqk,bhkd->bhqd", p, v)
        return (lambda x, *d: x.permute(*d))(o, 0, 2, 1, 3).reshape(B, Sq, Hq * Dh) @ wo

    def _B_ref(x, w_gate, w_up, w_down):
        g = torch.einsum("bsd,df->bsf", x, w_gate)
        u = torch.einsum("bsd,df->bsf", x, w_up)
        h = g * u
        return torch.einsum("bsf,fd->bsd", h, w_down)

    x = A_x
    g = _sigmoid((x * gate_w).sum(-1, keepdims=True))
    a = _A_ref(x, A_k_cache, A_v_cache, A_wq, A_wo)
    b = _B_ref(x, B_w_gate, B_w_up, B_w_down)
    return g * a + (1 - g) * b
```

```cpp
#include <cuda_runtime.h>
#include <cuda_bf16.h>
#include <stdint.h>

namespace {

constexpr int D_MODEL = 512;
constexpr int NHEAD   = 32;
constexpr int SK      = 4096;
constexpr int DH      = 128;
constexpr int WIN     = 1024;
constexpr int FF      = 1376;
constexpr int NUNIT   = FF / 32;
constexpr int NCTA    = 128;
constexpr int NTHREADS = 13 * 32;

constexpr uint32_t TILE     = 32768;
constexpr uint32_t OFF_V01  = 0;
constexpr uint32_t OFF_K    = 2 * TILE;
constexpr uint32_t OFF_WO   = OFF_K + 2 * TILE;
constexpr uint32_t OFF_MISC = OFF_K + 4 * TILE + 512;
constexpr uint32_t OFF_OPART = OFF_MISC;
constexpr uint32_t OFF_QPART = OFF_OPART + 8192;
constexpr uint32_t OFF_FPART = OFF_QPART + 2048;
constexpr uint32_t OFF_GU    = OFF_FPART + 2048;
constexpr uint32_t OFF_Q     = OFF_GU + 512;
constexpr uint32_t OFF_O     = OFF_Q + 256;
constexpr uint32_t OFF_STAT  = OFF_O + 256;
constexpr uint32_t OFF_BAR   = OFF_STAT + 128;
constexpr uint32_t SMEM_BYTES = OFF_BAR + 256;
enum { B_K = 0, B_V = 4, B_WO = 8, B_KFREE = 12, B_Q = 15, B_STAT = 16, B_O = 17, B_F = 18, B_COUNT = 19 };

constexpr int SPIN_LIMIT = 1 << 22;

__device__ uint4 g_partA[NCTA * NHEAD * 2];
__device__ uint4 g_partF[NCTA * NUNIT * 2];

#define PROF(ev) do {} while (0)

__device__ __forceinline__ void mbar_init(uint32_t a, uint32_t c) {
    asm volatile("mbarrier.init.shared::cta.b64 [%0], %1;" :: "r"(a), "r"(c) : "memory");
}
__device__ __forceinline__ void mbar_expect(uint32_t a, uint32_t bytes) {
    asm volatile("mbarrier.arrive.expect_tx.shared::cta.b64 _, [%0], %1;" :: "r"(a), "r"(bytes) : "memory");
}
__device__ __forceinline__ void mbar_arrive(uint32_t a) {
    asm volatile("mbarrier.arrive.shared::cta.b64 _, [%0];" :: "r"(a) : "memory");
}
__device__ __forceinline__ void mbar_wait(uint32_t a) {
    uint32_t ok; int it = 0;
    do {
        asm volatile("{.reg .pred p; mbarrier.try_wait.parity.shared::cta.b64 p, [%1], 0; selp.u32 %0, 1, 0, p;}"
                     : "=r"(ok) : "r"(a) : "memory");
    } while (!ok && ++it < SPIN_LIMIT);
}
__device__ __forceinline__ void mbar_wait_cluster(uint32_t a) {
    uint32_t ok; int it = 0;
    do {
        asm volatile("{.reg .pred p; mbarrier.try_wait.parity.acquire.cluster.shared::cta.b64 p, [%1], 0; selp.u32 %0, 1, 0, p;}"
                     : "=r"(ok) : "r"(a) : "memory");
    } while (!ok && ++it < SPIN_LIMIT);
}
__device__ __forceinline__ void bulk_g2s(uint32_t dst, const void* src, uint32_t bytes, uint32_t mbar) {
    asm volatile("cp.async.bulk.shared::cluster.global.mbarrier::complete_tx::bytes [%0], [%1], %2, [%3];"
                 :: "r"(dst), "l"(src), "r"(bytes), "r"(mbar) : "memory");
}
__device__ __forceinline__ void bulk_g2s_stream(uint32_t dst, const void* src, uint32_t bytes, uint32_t mbar, uint64_t pol) {
    asm volatile("cp.async.bulk.shared::cluster.global.mbarrier::complete_tx::bytes.L2::cache_hint [%0], [%1], %2, [%3], %4;"
                 :: "r"(dst), "l"(src), "r"(bytes), "r"(mbar), "l"(pol) : "memory");
}
__device__ __forceinline__ uint32_t mapa(uint32_t a, uint32_t rank) {
    uint32_t r; asm("mapa.shared::cluster.u32 %0, %1, %2;" : "=r"(r) : "r"(a), "r"(rank)); return r;
}
__device__ __forceinline__ void st_async_b32(uint32_t a, uint32_t v, uint32_t mbar) {
    asm volatile("st.async.shared::cluster.mbarrier::complete_tx::bytes.b32 [%0], %1, [%2];" :: "r"(a), "r"(v), "r"(mbar) : "memory");
}
__device__ __forceinline__ void st_async_v2(uint32_t a, float x, float y, uint32_t mbar) {
    asm volatile("st.async.shared::cluster.mbarrier::complete_tx::bytes.v2.f32 [%0], {%1, %2}, [%3];" :: "r"(a), "f"(x), "f"(y), "r"(mbar) : "memory");
}
__device__ __forceinline__ void st_async_v4(uint32_t a, float x, float y, float z, float w, uint32_t mbar) {
    asm volatile("st.async.shared::cluster.mbarrier::complete_tx::bytes.v4.f32 [%0], {%1, %2, %3, %4}, [%5];"
                 :: "r"(a), "f"(x), "f"(y), "f"(z), "f"(w), "r"(mbar) : "memory");
}
__device__ __forceinline__ uint4 ldg128(const void* p) {
    uint4 v;
    asm volatile("ld.global.nc.L1::no_allocate.v4.u32 {%0,%1,%2,%3}, [%4];" : "=r"(v.x), "=r"(v.y), "=r"(v.z), "=r"(v.w) : "l"(p));
    return v;
}
__device__ __forceinline__ uint4 lds128(uint32_t a) {
    uint4 v;
    asm volatile("ld.shared.v4.u32 {%0,%1,%2,%3}, [%4];" : "=r"(v.x), "=r"(v.y), "=r"(v.z), "=r"(v.w) : "r"(a) : "memory");
    return v;
}
__device__ __forceinline__ float lds32f(uint32_t a) {
    float v; asm volatile("ld.shared.f32 %0, [%1];" : "=f"(v) : "r"(a) : "memory"); return v;
}
__device__ __forceinline__ float2 lds64f(uint32_t a) {
    float2 v; asm volatile("ld.shared.v2.f32 {%0,%1}, [%2];" : "=f"(v.x), "=f"(v.y) : "r"(a) : "memory"); return v;
}
__device__ __forceinline__ void sts128f(uint32_t a, float x, float y, float z, float w) {
    asm volatile("st.shared.v4.f32 [%0], {%1,%2,%3,%4};" :: "r"(a), "f"(x), "f"(y), "f"(z), "f"(w) : "memory");
}
__device__ __forceinline__ uint4 ld_poll(const uint4* p) {
    uint4 v;
    asm volatile("ld.relaxed.gpu.global.v4.u32 {%0,%1,%2,%3}, [%4];" : "=r"(v.x), "=r"(v.y), "=r"(v.z), "=r"(v.w) : "l"(p) : "memory");
    return v;
}
__device__ __forceinline__ void st_post(uint4* p, uint32_t x, uint32_t y, uint32_t z, uint32_t w) {
    asm volatile("st.relaxed.gpu.global.v4.u32 [%0], {%1,%2,%3,%4};" :: "l"(p), "r"(x), "r"(y), "r"(z), "r"(w) : "memory");
}
__device__ __forceinline__ uint32_t nz(float v) {
    uint32_t u = __float_as_uint(v); return u == 0u ? 0x80000000u : u;
}
__device__ __forceinline__ bool full4(const uint4& v) { return v.x != 0u && v.y != 0u && v.z != 0u && v.w != 0u; }
__device__ __forceinline__ void mma16816(float (&c)[4], uint32_t a0, uint32_t a1, uint32_t a2, uint32_t a3, uint32_t b0, uint32_t b1) {
    asm volatile("mma.sync.aligned.m16n8k16.row.col.f32.bf16.bf16.f32 {%0,%1,%2,%3}, {%4,%5,%6,%7}, {%8,%9}, {%0,%1,%2,%3};"
                 : "+f"(c[0]), "+f"(c[1]), "+f"(c[2]), "+f"(c[3]) : "r"(a0), "r"(a1), "r"(a2), "r"(a3), "r"(b0), "r"(b1));
}
__device__ __forceinline__ uint32_t pack_bf16(float lo, float hi) {
    uint32_t r; asm("cvt.rn.bf16x2.f32 %0, %1, %2;" : "=r"(r) : "f"(hi), "f"(lo)); return r;
}
__device__ __forceinline__ float rbf(float v) { return __bfloat162float(__float2bfloat16_rn(v)); }
__device__ __forceinline__ float bf_lo(uint32_t u) { return __uint_as_float(u << 16); }
__device__ __forceinline__ float bf_hi(uint32_t u) { return __uint_as_float(u & 0xFFFF0000u); }
__device__ __forceinline__ void named_bar(int id, int n) { asm volatile("bar.sync %0, %1;" :: "r"(id), "r"(n) : "memory"); }

__device__ __forceinline__ void gemv_step(float (&c0)[4], float (&c1)[4], const uint4& wa, const uint4& wb,
                                          uint32_t xr, uint32_t sel_lo, uint32_t sel_hi) {
    uint32_t b0 = __byte_perm(xr, 0u, sel_lo), b1 = __byte_perm(xr, 0u, sel_hi);
    mma16816(c0, wa.x, wa.y, wb.x, wb.y, b0, b1);
    mma16816(c1, wa.z, wa.w, wb.z, wb.w, b0, b1);
}

__global__ void __cluster_dims__(2, 1, 1) __launch_bounds__(NTHREADS, 1)
fused_decode_kernel(const __nv_bfloat16* __restrict__ x, const __nv_bfloat16* __restrict__ kc,
                    const __nv_bfloat16* __restrict__ vc, const __nv_bfloat16* __restrict__ wq,
                    const __nv_bfloat16* __restrict__ wo, const __nv_bfloat16* __restrict__ wg,
                    const __nv_bfloat16* __restrict__ wu, const __nv_bfloat16* __restrict__ wd,
                    const __nv_bfloat16* __restrict__ gate_w, __nv_bfloat16* __restrict__ out) {
    extern __shared__ __align__(128) unsigned char smem_raw[];
    const uint32_t sb = (uint32_t)__cvta_generic_to_shared(smem_raw);
    const int warp = threadIdx.x >> 5, lane = threadIdx.x & 31;
    const int g = lane >> 2, t = lane & 3;
    const int cta = blockIdx.x;
    const int s = cta & 1;
    const int cl = cta >> 1;
    const int b = cl & 1, h = cl >> 1;
    auto bar = [&](int i) { return sb + OFF_BAR + 8u * i; };
    const uint32_t sel_lo = (g & 1) ? 0x1044u : 0x4410u;
    const uint32_t sel_hi = (g & 1) ? 0x3244u : 0x4432u;

    if (warp < 8) {
        PROF(0);
        uint4 w[16];
        {
            const __nv_bfloat16* p = wq + (size_t)(warp * 64 + t * 16) * (NHEAD * DH) + h * DH + s * 64 + g * 8;
#pragma unroll
            for (int i = 0; i < 16; i++) w[i] = ldg128(p + (size_t)i * (NHEAD * DH));
        }
        const uint4 xa = ldg128(x + b * D_MODEL + warp * 64 + t * 16);
        const uint4 xb = ldg128(x + b * D_MODEL + warp * 64 + t * 16 + 8);
        asm volatile("barrier.cluster.arrive.relaxed.aligned;" ::: "memory");
        {
            float c0[4] = {0.f, 0.f, 0.f, 0.f}, c1[4] = {0.f, 0.f, 0.f, 0.f};
            gemv_step(c0, c1, w[0], w[1], xa.x, sel_lo, sel_hi);
            gemv_step(c0, c1, w[2], w[3], xa.y, sel_lo, sel_hi);
            gemv_step(c0, c1, w[4], w[5], xa.z, sel_lo, sel_hi);
            gemv_step(c0, c1, w[6], w[7], xa.w, sel_lo, sel_hi);
            gemv_step(c0, c1, w[8], w[9], xb.x, sel_lo, sel_hi);
            gemv_step(c0, c1, w[10], w[11], xb.y, sel_lo, sel_hi);
            gemv_step(c0, c1, w[12], w[13], xb.z, sel_lo, sel_hi);
            gemv_step(c0, c1, w[14], w[15], xb.w, sel_lo, sel_hi);
            if (t == 0) {
                const uint32_t a = sb + OFF_QPART + warp * 256 + g * 32;
                sts128f(a, c0[0], c0[1], c0[2], c0[3]);
                sts128f(a + 16, c1[0], c1[1], c1[2], c1[3]);
            }
        }
        asm volatile("barrier.cluster.wait.aligned;" ::: "memory");
        named_bar(1, 256);
        if (warp == 0) {
            PROF(1);
            float lo = 0.f, hi = 0.f;
#pragma unroll
            for (int i = 0; i < 8; i++) { float2 v = lds64f(sb + OFF_QPART + i * 256 + lane * 8); lo += v.x; hi += v.y; }
            const uint32_t qq = pack_bf16(lo, hi);
            const uint32_t a = sb + OFF_Q + s * 128 + lane * 4;
            st_async_b32(mapa(a, 0), qq, mapa(bar(B_Q), 0));
            st_async_b32(mapa(a, 1), qq, mapa(bar(B_Q), 1));
        }
        mbar_wait_cluster(bar(B_Q));
        if (warp == 0) PROF(2);
        uint4 qf[4];
#pragma unroll
        for (int j = 0; j < 4; j++) qf[j] = lds128(sb + OFF_Q + ((4 * (j ^ (g & 1)) + t) << 4));

        float sc[8];
#pragma unroll
        for (int T = 0; T < 4; T++) {
            mbar_wait(bar(B_K + T));
            if (warp == 0) PROF(3 + T);
            const uint32_t a = sb + OFF_K + T * TILE + (warp * 16 + g) * 256 + t * 16;
            uint4 kg[4], kh[4];
#pragma unroll
            for (int j = 0; j < 4; j++) {
                kg[j] = lds128(a + ((j ^ (g & 1)) << 6));
                kh[j] = lds128(a + 2048 + ((j ^ (g & 1)) << 6));
            }
            float c0[4] = {0.f, 0.f, 0.f, 0.f}, c1[4] = {0.f, 0.f, 0.f, 0.f};
#pragma unroll
            for (int j = 0; j < 4; j++) {
                mma16816(c0, kg[j].x, kh[j].x, kg[j].y, kh[j].y, qf[j].x, qf[j].y);
                mma16816(c1, kg[j].z, kh[j].z, kg[j].w, kh[j].w, qf[j].z, qf[j].w);
            }
            const float s_lo = (g & 1) ? c0[1] + c1[1] : c0[0] + c1[0];
            const float s_hi = (g & 1) ? c0[3] + c1[3] : c0[2] + c1[2];
            sc[2 * T]     = rbf(rbf(s_lo) * 0.08838834764831845f);
            sc[2 * T + 1] = rbf(rbf(s_hi) * 0.08838834764831845f);
            if (T != 2) {
                __syncwarp();
                if (lane == 0) mbar_arrive(bar(B_KFREE + (T == 3 ? 2 : T)));
            }
        }
        float m = sc[0];
#pragma unroll
        for (int i = 1; i < 8; i++) m = fmaxf(m, sc[i]);
        m = fmaxf(m, __shfl_xor_sync(0xffffffffu, m, 4));
        m = fmaxf(m, __shfl_xor_sync(0xffffffffu, m, 8));
        m = fmaxf(m, __shfl_xor_sync(0xffffffffu, m, 16));
        uint32_t pe[4], po[4];
        float l = 0.f;
        const float ms = (m == -INFINITY) ? 0.f : m;
#pragma unroll
        for (int T = 0; T < 4; T++) {
            const float p0 = exp2f((sc[2 * T] - ms) * 1.4426950408889634f);
            const float p1 = exp2f((sc[2 * T + 1] - ms) * 1.4426950408889634f);
            l += p0 + p1;
            const uint32_t pp = pack_bf16(p0, p1);
            const uint32_t nb = __shfl_xor_sync(0xffffffffu, pp, 4);
            pe[T] = (g & 1) ? nb : pp;
            po[T] = (g & 1) ? pp : nb;
        }
        l += __shfl_xor_sync(0xffffffffu, l, 4);
        l += __shfl_xor_sync(0xffffffffu, l, 8);
        l += __shfl_xor_sync(0xffffffffu, l, 16);
        if (lane < 2) st_async_v2(mapa(sb + OFF_STAT + (s * 8 + warp) * 8, lane), m, l, mapa(bar(B_STAT), lane));

        const bool diag = (t == (g >> 1));
        const uint32_t dsel_lo = diag ? sel_lo : 0x4444u, dsel_hi = diag ? sel_hi : 0x4444u;
        float acc[4][4];
#pragma unroll
        for (int i = 0; i < 4; i++) { acc[i][0] = acc[i][1] = acc[i][2] = acc[i][3] = 0.f; }
        float fscale = 0.f;
#pragma unroll
        for (int T = 0; T < 4; T++) {
            if (T == 3) {
                mbar_wait_cluster(bar(B_STAT));
                const float2 st = lds64f(sb + OFF_STAT + (lane & 15) * 8);
                float M = st.x;
#pragma unroll
                for (int o = 1; o < 16; o <<= 1) M = fmaxf(M, __shfl_xor_sync(0xffffffffu, M, o));
                float L = st.y * exp2f((st.x - M) * 1.4426950408889634f);
#pragma unroll
                for (int o = 1; o < 16; o <<= 1) L += __shfl_xor_sync(0xffffffffu, L, o);
                fscale = exp2f((m - M) * 1.4426950408889634f) / L;
            }
            mbar_wait(bar(B_V + T));
            if (warp == 0) PROF(7 + T);
            const uint32_t a = sb + OFF_V01 + T * TILE + (warp * 16 + 2 * t) * 256 + ((g ^ (2 * t)) << 4);
            uint4 va[4], vb[4];
#pragma unroll
            for (int i = 0; i < 4; i++) {
                va[i] = lds128(a + (i >> 1) * 256 + (i & 1) * 128);
                vb[i] = lds128(a + 2048 + (i >> 1) * 256 + (i & 1) * 128);
            }
            gemv_step(acc[0], acc[1], va[0], vb[0], pe[T], dsel_lo, dsel_hi);
            gemv_step(acc[2], acc[3], va[1], vb[1], pe[T], dsel_lo, dsel_hi);
            gemv_step(acc[0], acc[1], va[2], vb[2], po[T], dsel_lo, dsel_hi);
            gemv_step(acc[2], acc[3], va[3], vb[3], po[T], dsel_lo, dsel_hi);
        }
        {
            float r[8];
#pragma unroll
            for (int i = 0; i < 8; i++) {
                const float lo = acc[i >> 2][i & 3], hi = acc[2 + (i >> 2)][i & 3];
                const float send = (t & 1) ? lo : hi, keep = (t & 1) ? hi : lo;
                r[i] = keep + __shfl_xor_sync(0xffffffffu, send, 9);
            }
            float q4[4];
#pragma unroll
            for (int i = 0; i < 4; i++) {
                const float send = (t & 2) ? r[i] : r[4 + i], keep = (t & 2) ? r[4 + i] : r[i];
                q4[i] = (keep + __shfl_xor_sync(0xffffffffu, send, 18)) * fscale;
            }
            const int dim = (t & 1) * 64 + (g ^ (2 * t)) * 8 + (t >> 1) * 4;
            const uint32_t a = sb + OFF_OPART + (s * 8 + warp) * 512 + dim * 4;
            st_async_v4(mapa(a, 0), q4[0], q4[1], q4[2], q4[3], mapa(bar(B_O), 0));
            st_async_v4(mapa(a, 1), q4[0], q4[1], q4[2], q4[3], mapa(bar(B_O), 1));
        }
        if (warp >= 4) return;
        mbar_wait_cluster(bar(B_O));
        if (warp == 0) PROF(11);
        {
            float v[16];
#pragma unroll
            for (int i = 0; i < 16; i++) v[i] = lds32f(sb + OFF_OPART + i * 512 + threadIdx.x * 4);
#pragma unroll
            for (int o = 8; o > 0; o >>= 1)
#pragma unroll
                for (int i = 0; i < o; i++) v[i] += v[i + o];
            const unsigned short ob = __bfloat16_as_ushort(__float2bfloat16_rn(v[0]));
            asm volatile("st.shared.u16 [%0], %1;" :: "r"(sb + OFF_O + threadIdx.x * 2), "h"(ob) : "memory");
        }
        named_bar(2, 128);
        uint4 of[4];
#pragma unroll
        for (int T = 0; T < 4; T++) of[T] = lds128(sb + OFF_O + T * 64 + t * 16);
        if (warp == 0) PROF(12);
        float c0[4] = {0.f, 0.f, 0.f, 0.f}, c1[4] = {0.f, 0.f, 0.f, 0.f};
        float c2[4] = {0.f, 0.f, 0.f, 0.f}, c3[4] = {0.f, 0.f, 0.f, 0.f};
#pragma unroll
        for (int T = 0; T < 4; T++) {
            mbar_wait(bar(B_WO + T));
            if (warp == 0) PROF(13 + T);
            const uint32_t a = sb + OFF_WO + T * (32 * 512 + 128) + t * (8 * 512 + 32) + warp * 128 + g * 16;
            uint4 ww[8];
#pragma unroll
            for (int i = 0; i < 8; i++) ww[i] = lds128(a + i * 512);
            gemv_step(c0, c1, ww[0], ww[1], of[T].x, sel_lo, sel_hi);
            gemv_step(c2, c3, ww[2], ww[3], of[T].y, sel_lo, sel_hi);
            gemv_step(c0, c1, ww[4], ww[5], of[T].z, sel_lo, sel_hi);
            gemv_step(c2, c3, ww[6], ww[7], of[T].w, sel_lo, sel_hi);
        }
        if (t < 2) {
            float r[4];
#pragma unroll
            for (int i = 0; i < 4; i++) r[i] = t ? c1[i] + c3[i] : c0[i] + c2[i];
            const int cg = s * 32 + warp * 8 + g;
            st_post(&g_partA[((b * 64 + cg) * NHEAD + h) * 2 + t], nz(r[0]), nz(r[1]), nz(r[2]), nz(r[3]));
        }
        if (warp == 0) PROF(17);
    } else if (warp == 8) {
        const size_t kvoff = ((size_t)(b * NHEAD + h) * SK + (SK - WIN) + s * (WIN / 2)) * DH;
        const char* kp = (const char*)(kc + kvoff);
        const char* vp = (const char*)(vc + kvoff);
        uint64_t pol;
        asm volatile("createpolicy.fractional.L2::evict_first.b64 %0, 1.0;" : "=l"(pol));
        if (lane < B_COUNT) {
            const bool kfree = lane >= B_KFREE && lane < B_Q;
            mbar_init(bar(lane), kfree ? 8 : 1);
            asm volatile("fence.mbarrier_init.release.cluster;" ::: "memory");
            asm volatile("fence.proxy.async.shared::cta;" ::: "memory");
            if (!kfree) {
                const uint32_t bytes = lane < B_WO ? TILE : lane < B_KFREE ? 16384u : lane == B_Q ? 256u
                                     : lane == B_STAT ? 128u : lane == B_O ? 8192u : 512u;
                mbar_expect(bar(lane), bytes);
            }
        }
        __syncwarp();
        if (lane == 0) {
#pragma unroll
            for (int T = 0; T < 4; T++) bulk_g2s_stream(sb + OFF_K + T * TILE, kp + T * TILE, TILE, bar(B_K + T), pol);
#pragma unroll
            for (int T = 0; T < 2; T++) bulk_g2s_stream(sb + OFF_V01 + T * TILE, vp + T * TILE, TILE, bar(B_V + T), pol);
        }
        __syncwarp();
        asm volatile("barrier.cluster.arrive.release.aligned;" ::: "memory");
        const int rb = cta >> 6;
        float gate;
        {
            const uint4 x0 = ldg128(x + rb * D_MODEL + lane * 16), x1 = ldg128(x + rb * D_MODEL + lane * 16 + 8);
            const uint4 g0 = ldg128(gate_w + lane * 16), g1 = ldg128(gate_w + lane * 16 + 8);
            const uint32_t xv[8] = {x0.x, x0.y, x0.z, x0.w, x1.x, x1.y, x1.z, x1.w};
            const uint32_t gv[8] = {g0.x, g0.y, g0.z, g0.w, g1.x, g1.y, g1.z, g1.w};
            float z = 0.f;
#pragma unroll
            for (int i = 0; i < 8; i++) z += rbf(bf_lo(xv[i]) * bf_lo(gv[i])) + rbf(bf_hi(xv[i]) * bf_hi(gv[i]));
#pragma unroll
            for (int o = 16; o > 0; o >>= 1) z += __shfl_xor_sync(0xffffffffu, z, o);
            z = rbf(z);
            gate = rbf(1.f / (1.f + __expf(-z)));
        }
        asm volatile("barrier.cluster.wait.aligned;" ::: "memory");
#pragma unroll
        for (int T = 0; T < 2; T++) {
            mbar_wait(bar(B_KFREE + T));
            if (lane == 0) bulk_g2s_stream(sb + OFF_K + T * TILE, vp + (2 + T) * TILE, TILE, bar(B_V + 2 + T), pol);
        }
        mbar_wait(bar(B_KFREE + 2));
        {
            const char* wp = (const char*)(wo + (size_t)(h * DH + lane) * D_MODEL + s * 256);
            const uint32_t dst = sb + OFF_WO + lane * 512 + (lane >> 3) * 32;
#pragma unroll
            for (int T = 0; T < 4; T++) {
                bulk_g2s(dst + T * (32 * 512 + 128), wp + T * (32 * D_MODEL * 2), 512, bar(B_WO + T));
                __syncwarp();
            }
        }
        PROF(18);
        float fb[4];
        {
            mbar_wait(bar(B_V + 1));
            uint4* p = g_partF + cta * (NUNIT * 2) + lane;
            const bool has3 = lane < NUNIT * 2 - 64;
            uint4 v0, v1, v2 = make_uint4(0x80000000u, 0x80000000u, 0x80000000u, 0x80000000u);
            int it = 0; bool ok;
            do {
                v0 = ld_poll(p); v1 = ld_poll(p + 32);
                if (has3) v2 = ld_poll(p + 64);
                ok = full4(v0) && full4(v1) && full4(v2);
            } while (!__all_sync(0xffffffffu, ok) && ++it < SPIN_LIMIT);
            st_post(p, 0u, 0u, 0u, 0u); st_post(p + 32, 0u, 0u, 0u, 0u);
            if (has3) st_post(p + 64, 0u, 0u, 0u, 0u);
            fb[0] = __uint_as_float(v0.x) + __uint_as_float(v1.x) + __uint_as_float(v2.x);
            fb[1] = __uint_as_float(v0.y) + __uint_as_float(v1.y) + __uint_as_float(v2.y);
            fb[2] = __uint_as_float(v0.z) + __uint_as_float(v1.z) + __uint_as_float(v2.z);
            fb[3] = __uint_as_float(v0.w) + __uint_as_float(v1.w) + __uint_as_float(v2.w);
            const float omg = rbf(1.f - gate);
#pragma unroll
            for (int i = 0; i < 4; i++) {
#pragma unroll
                for (int o = 2; o < 32; o <<= 1) fb[i] += __shfl_xor_sync(0xffffffffu, fb[i], o);
                fb[i] = rbf(omg * rbf(fb[i]));
            }
        }
        PROF(19);
        {
            mbar_wait(bar(B_WO + 3));
            uint4* p = g_partA + cta * (NHEAD * 2) + lane;
            uint4 v0, v1;
            int it = 0; bool ok;
            do {
                v0 = ld_poll(p); v1 = ld_poll(p + 32);
                ok = full4(v0) && full4(v1);
            } while (!__all_sync(0xffffffffu, ok) && ++it < SPIN_LIMIT);
            PROF(20);
            float fa[4];
            fa[0] = __uint_as_float(v0.x) + __uint_as_float(v1.x);
            fa[1] = __uint_as_float(v0.y) + __uint_as_float(v1.y);
            fa[2] = __uint_as_float(v0.z) + __uint_as_float(v1.z);
            fa[3] = __uint_as_float(v0.w) + __uint_as_float(v1.w);
#pragma unroll
            for (int o = 2; o < 32; o <<= 1)
#pragma unroll
                for (int i = 0; i < 4; i++) fa[i] += __shfl_xor_sync(0xffffffffu, fa[i], o);
            if (lane < 2) {
                uint2 r;
                r.x = pack_bf16(rbf(gate * rbf(fa[0])) + fb[0], rbf(gate * rbf(fa[1])) + fb[1]);
                r.y = pack_bf16(rbf(gate * rbf(fa[2])) + fb[2], rbf(gate * rbf(fa[3])) + fb[3]);
                *reinterpret_cast<uint2*>(out + cta * 8 + lane * 4) = r;
            }
            st_post(p, 0u, 0u, 0u, 0u); st_post(p + 32, 0u, 0u, 0u, 0u);
            PROF(21);
        }
    } else {
        if (cl >= NUNIT) {
            asm volatile("barrier.cluster.arrive.relaxed.aligned;" ::: "memory");
            return;
        }
        const int fw = warp - 9;
        uint4 w[16], wdn[8];
        const int row0 = fw * 128 + (g >> 2) * 64 + t * 16;
        {
            const __nv_bfloat16* p = (s ? wu : wg) + (size_t)row0 * FF + cl * 32 + (g & 3) * 8;
#pragma unroll
            for (int i = 0; i < 16; i++) w[i] = ldg128(p + (size_t)i * FF);
        }
        const uint4 xa = ldg128(x + ((g >> 1) & 1) * D_MODEL + row0);
        const uint4 xb = ldg128(x + ((g >> 1) & 1) * D_MODEL + row0 + 8);
        {
            const __nv_bfloat16* p = wd + (size_t)(cl * 32 + t * 8) * D_MODEL + s * 256 + fw * 64 + g * 8;
#pragma unroll
            for (int i = 0; i < 8; i++) wdn[i] = ldg128(p + (size_t)i * D_MODEL);
        }
        asm volatile("barrier.cluster.arrive.relaxed.aligned;" ::: "memory");
        {
            float c0[4] = {0.f, 0.f, 0.f, 0.f}, c1[4] = {0.f, 0.f, 0.f, 0.f};
            gemv_step(c0, c1, w[0], w[1], xa.x, sel_lo, sel_hi);
            gemv_step(c0, c1, w[2], w[3], xa.y, sel_lo, sel_hi);
            gemv_step(c0, c1, w[4], w[5], xa.z, sel_lo, sel_hi);
            gemv_step(c0, c1, w[6], w[7], xa.w, sel_lo, sel_hi);
            gemv_step(c0, c1, w[8], w[9], xb.x, sel_lo, sel_hi);
            gemv_step(c0, c1, w[10], w[11], xb.y, sel_lo, sel_hi);
            gemv_step(c0, c1, w[12], w[13], xb.z, sel_lo, sel_hi);
            gemv_step(c0, c1, w[14], w[15], xb.w, sel_lo, sel_hi);
            if ((t >> 1) == (g >> 2)) {
                const uint32_t a = sb + OFF_FPART + (fw * 2 + (g >> 2)) * 256 + (t & 1) * 128 + (g & 3) * 32;
                sts128f(a, c0[0], c0[1], c0[2], c0[3]);
                sts128f(a + 16, c1[0], c1[1], c1[2], c1[3]);
            }
        }
        asm volatile("barrier.cluster.wait.aligned;" ::: "memory");
        named_bar(3, 128);
        if (fw == 0) {
            float lo = 0.f, hi = 0.f;
#pragma unroll
            for (int i = 0; i < 8; i++) { float2 v = lds64f(sb + OFF_FPART + i * 256 + lane * 8); lo += v.x; hi += v.y; }
            lo = rbf(lo); hi = rbf(hi);
            const uint32_t a = sb + OFF_GU + s * 256 + lane * 8;
            st_async_v2(mapa(a, 0), lo, hi, mapa(bar(B_F), 0));
            st_async_v2(mapa(a, 1), lo, hi, mapa(bar(B_F), 1));
        }
        mbar_wait_cluster(bar(B_F));
        {
            const uint32_t a = sb + OFF_GU + ((g >> 1) & 1) * 128 + t * 32;
            const uint4 ga = lds128(a), gb = lds128(a + 16), ua = lds128(a + 256), ub = lds128(a + 272);
            const uint32_t h0 = pack_bf16(__uint_as_float(ga.x) * __uint_as_float(ua.x), __uint_as_float(ga.y) * __uint_as_float(ua.y));
            const uint32_t h1 = pack_bf16(__uint_as_float(ga.z) * __uint_as_float(ua.z), __uint_as_float(ga.w) * __uint_as_float(ua.w));
            const uint32_t h2 = pack_bf16(__uint_as_float(gb.x) * __uint_as_float(ub.x), __uint_as_float(gb.y) * __uint_as_float(ub.y));
            const uint32_t h3 = pack_bf16(__uint_as_float(gb.z) * __uint_as_float(ub.z), __uint_as_float(gb.w) * __uint_as_float(ub.w));
            float c0[4] = {0.f, 0.f, 0.f, 0.f}, c1[4] = {0.f, 0.f, 0.f, 0.f};
            gemv_step(c0, c1, wdn[0], wdn[1], h0, sel_lo, sel_hi);
            gemv_step(c0, c1, wdn[2], wdn[3], h1, sel_lo, sel_hi);
            gemv_step(c0, c1, wdn[4], wdn[5], h2, sel_lo, sel_hi);
            gemv_step(c0, c1, wdn[6], wdn[7], h3, sel_lo, sel_hi);
            float r[4];
#pragma unroll
            for (int i = 0; i < 4; i++) r[i] = (t >> 1) ? c1[i] : c0[i];
            const int cg = s * 32 + fw * 8 + g;
            st_post(&g_partF[(((t & 1) * 64 + cg) * NUNIT + cl) * 2 + (t >> 1)], nz(r[0]), nz(r[1]), nz(r[2]), nz(r[3]));
        }
        if (fw == 0) PROF(22);
    }
}

}

extern "C" void kernel_launch(void* const* d_in, const int* in_sizes, int n_in, void* d_out, int out_size) {
    (void)in_sizes; (void)n_in; (void)out_size;
    static bool attr_set = false;
    if (!attr_set) {
        cudaFuncSetAttribute(fused_decode_kernel, cudaFuncAttributeMaxDynamicSharedMemorySize, (int)SMEM_BYTES);
        attr_set = true;
    }
    typedef const __nv_bfloat16* P;
    fused_decode_kernel<<<NCTA, NTHREADS, SMEM_BYTES>>>((P)d_in[0], (P)d_in[1], (P)d_in[2], (P)d_in[3], (P)d_in[4],
                                                        (P)d_in[6], (P)d_in[7], (P)d_in[8], (P)d_in[9],
                                                        (__nv_bfloat16*)d_out);
}
```

```cpp
#include <cuda_runtime.h>
#include <cuda.h>
#include <cuda_bf16.h>
#include <stdint.h>
#include <type_traits>

namespace {

constexpr int D_MODEL = 512;
constexpr int NHEAD   = 32;
constexpr int SK      = 4096;
constexpr int DH      = 128;
constexpr int WIN     = 1024;
constexpr int FF      = 1376;
constexpr int NUNIT   = FF / 32;
constexpr int NCTA    = 128;
constexpr int NTHREADS = 14 * 32;

constexpr uint32_t CH = 16384;
enum { C_WQ = 0, C_K = 4, C_V = 12, C_WO = 20, C_GU = 24, C_WD = 26, C_COUNT = 27 };
#define P0 7
#define P1 11
#define P2 16
#define WT_FFN 0
#define ORDER 4
#define PFM 1
#define KF 2
__host__ __device__ constexpr int chunk_at(int i) {
    if (i < KF) return C_K + i;
    if (i < KF + 4) return C_WQ + i - KF;
    return i == P0 ? C_GU : i == P1 ? C_GU + 1 : i == P2 ? C_WD : i - (i > P0) - (i > P1) - (i > P2);
}
__host__ __device__ constexpr int pos_of(int c) { int i = 0; while (chunk_at(i) != c) i++; return i; }
__host__ __device__ constexpr unsigned long long slot_tab(int c0) {
    unsigned long long v = 0;
    for (int c = c0; c < c0 + 16 && c < C_COUNT; c++) v |= (unsigned long long)(pos_of(c) % 13) << (4 * (c - c0));
    return v;
}
constexpr unsigned long long SLOT_LO = slot_tab(0), SLOT_HI = slot_tab(16);
constexpr bool V_REUSED = pos_of(C_V) + 13 < C_COUNT, WD_REUSED = pos_of(C_WD) + 13 < C_COUNT;
__host__ __device__ constexpr uint32_t slot(int c) { return (uint32_t)(((c < 16 ? SLOT_LO : SLOT_HI) >> (4 * (c & 15))) & 15) * CH; }
#define WT_DUP 1
__host__ __device__ constexpr int chunk_wt(int c) { return (c < C_K || (c >= C_WO && c < C_GU)) ? WT_DUP : c >= C_GU ? WT_FFN : 2; }
constexpr uint32_t OFF_MISC = 13 * CH;
constexpr uint32_t OFF_OPART = OFF_MISC;
constexpr uint32_t OFF_QPART = OFF_OPART + 8192;
constexpr uint32_t OFF_FPART = OFF_QPART + 2048;
constexpr uint32_t OFF_GU    = OFF_FPART + 2048;
constexpr uint32_t OFF_Q     = OFF_GU + 512;
constexpr uint32_t OFF_O     = OFF_Q + 256;
constexpr uint32_t OFF_STAT  = OFF_O + 256;
constexpr uint32_t OFF_BAR   = OFF_STAT + 128;
constexpr uint32_t SMEM_BYTES = OFF_BAR + 512;
enum { B_Q = C_COUNT, B_STAT, B_O, B_F, B_WQFREE, B_GUFREE, B_WDFREE, B_KFREE, B_VFREE = B_KFREE + 8, B_COUNT = B_VFREE + 2 };
#define WIN_F 6
#define WIN_END WIN_F
#define WIN_0 8
#define WIN_N 6
#define QSWAP 0
#define PROMO CU_TENSOR_MAP_L2_PROMOTION_NONE
#define WSWAP 0
struct Sched { uint32_t e[32]; int n, n0; };
__host__ __device__ constexpr Sched make_sched(bool ffn) {
    Sched S{}; int hist[C_COUNT] = {}; int n = 0, landed = 0, infl = 0; S.n0 = -1;
    for (int i = 0; i < C_COUNT; i++) {
        const int c = chunk_at(i);
        if (!ffn && c >= C_GU) continue;
        const int W = (c >= C_WO && c < C_GU) ? WIN_END : S.n0 < 0 ? WIN_0 : ffn ? WIN_F : WIN_N;
        int land = -1, fr = -1;
        infl += chunk_wt(c);
        while (infl > W && landed < n) { land = hist[landed++]; infl -= chunk_wt(land); }
        if (i >= 13) {
            int pc = chunk_at(i - 13);
            if (!ffn && pc >= C_GU) pc = i >= 26 ? chunk_at(i - 26) : -1;
            if (pc >= 0) fr = pc < C_K ? B_WQFREE : pc < C_V ? B_KFREE + pc - C_K : pc < C_WO ? B_VFREE + pc - C_V
                            : pc < C_WD ? B_GUFREE : B_WDFREE;
        }
        if (S.n0 < 0 && (land >= 0 || fr >= 0 || c >= C_V)) S.n0 = n;
        S.e[n] = (uint32_t)c | (uint32_t)(land + 1) << 8 | (uint32_t)(fr + 1) << 16 | (uint32_t)(i % 13) << 24;
        hist[n++] = c;
    }
    S.n = n;
    return S;
}
constexpr int N0 = make_sched(true).n0 < make_sched(false).n0 ? make_sched(true).n0 : make_sched(false).n0;
static_assert(N0 >= KF + 4, "initial burst covers wq");
template <int I> struct SchedSel {
    static __device__ __forceinline__ uint32_t get(int lane, bool ffn) {
        constexpr uint32_t ef = make_sched(true).e[I], en = make_sched(false).e[I];
        const uint32_t rest = SchedSel<I + 1>::get(lane, ffn);
        return lane == I ? (ffn ? ef : en) : rest;
    }
};
template <> struct SchedSel<C_COUNT> { static __device__ __forceinline__ uint32_t get(int, bool) { return 0u; } };

constexpr int SPIN_LIMIT = 1 << 20;

__device__ uint4 g_partA[NCTA * NHEAD * 2];
__device__ uint4 g_partF[NCTA * NUNIT * 2];

#define PROF(ev) do {} while (0)

__device__ __forceinline__ void mbar_init(uint32_t a, uint32_t c) {
    asm volatile("mbarrier.init.shared::cta.b64 [%0], %1;" :: "r"(a), "r"(c) : "memory");
}
__device__ __forceinline__ void mbar_expect(uint32_t a, uint32_t bytes) {
    asm volatile("mbarrier.arrive.expect_tx.shared::cta.b64 _, [%0], %1;" :: "r"(a), "r"(bytes) : "memory");
}
__device__ __forceinline__ void mbar_arrive(uint32_t a) {
    asm volatile("mbarrier.arrive.shared::cta.b64 _, [%0];" :: "r"(a) : "memory");
}
__device__ __forceinline__ void mbar_wait(uint32_t a) {
    uint32_t ok; int it = 0;
    do {
        asm volatile("{.reg .pred p; mbarrier.try_wait.parity.shared::cta.b64 p, [%1], 0; selp.u32 %0, 1, 0, p;}"
                     : "=r"(ok) : "r"(a) : "memory");
    } while (!ok && ++it < SPIN_LIMIT);
}
__device__ __forceinline__ bool mbar_test(uint32_t a) {
    uint32_t ok;
    asm volatile("{.reg .pred p; mbarrier.test_wait.parity.shared::cta.b64 p, [%1], 0; selp.u32 %0, 1, 0, p;}"
                 : "=r"(ok) : "r"(a) : "memory");
    return ok != 0;
}
__device__ __forceinline__ void bulk_g2s_stream(uint32_t dst, const void* src, uint32_t bytes, uint32_t mbar, uint64_t pol) {
    asm volatile("cp.async.bulk.shared::cluster.global.mbarrier::complete_tx::bytes.L2::cache_hint [%0], [%1], %2, [%3], %4;"
                 :: "r"(dst), "l"(src), "r"(bytes), "r"(mbar), "l"(pol) : "memory");
}
__device__ __forceinline__ void tma3d(uint32_t dst, const CUtensorMap* map, int row, int blk, uint32_t mbar) {
    asm volatile("cp.async.bulk.tensor.3d.shared::cluster.global.mbarrier::complete_tx::bytes [%0], [%1, {%5, %2, %3}], [%4];"
                 :: "r"(dst), "l"(map), "r"(row), "r"(blk), "r"(mbar), "r"(0) : "memory");
}
__device__ __forceinline__ uint32_t mapa(uint32_t a, uint32_t rank) {
    uint32_t r; asm("mapa.shared::cluster.u32 %0, %1, %2;" : "=r"(r) : "r"(a), "r"(rank)); return r;
}
__device__ __forceinline__ void st_async_b32(uint32_t a, uint32_t v, uint32_t mbar) {
    asm volatile("st.async.shared::cluster.mbarrier::complete_tx::bytes.b32 [%0], %1, [%2];" :: "r"(a), "r"(v), "r"(mbar) : "memory");
}
__device__ __forceinline__ void st_async_v2(uint32_t a, float x, float y, uint32_t mbar) {
    asm volatile("st.async.shared::cluster.mbarrier::complete_tx::bytes.v2.f32 [%0], {%1, %2}, [%3];" :: "r"(a), "f"(x), "f"(y), "r"(mbar) : "memory");
}
__device__ __forceinline__ void st_async_v4(uint32_t a, float x, float y, float z, float w, uint32_t mbar) {
    asm volatile("st.async.shared::cluster.mbarrier::complete_tx::bytes.v4.f32 [%0], {%1, %2, %3, %4}, [%5];"
                 :: "r"(a), "f"(x), "f"(y), "f"(z), "f"(w), "r"(mbar) : "memory");
}
__device__ __forceinline__ uint4 ldg128(const void* p) {
    uint4 v;
    asm volatile("ld.global.nc.L1::no_allocate.v4.u32 {%0,%1,%2,%3}, [%4];" : "=r"(v.x), "=r"(v.y), "=r"(v.z), "=r"(v.w) : "l"(p));
    return v;
}
__device__ __forceinline__ uint4 lds128(uint32_t a) {
    uint4 v;
    asm volatile("ld.shared.v4.u32 {%0,%1,%2,%3}, [%4];" : "=r"(v.x), "=r"(v.y), "=r"(v.z), "=r"(v.w) : "r"(a) : "memory");
    return v;
}
__device__ __forceinline__ float lds32f(uint32_t a) {
    float v; asm volatile("ld.shared.f32 %0, [%1];" : "=f"(v) : "r"(a) : "memory"); return v;
}
__device__ __forceinline__ float2 lds64f(uint32_t a) {
    float2 v; asm volatile("ld.shared.v2.f32 {%0,%1}, [%2];" : "=f"(v.x), "=f"(v.y) : "r"(a) : "memory"); return v;
}
__device__ __forceinline__ void sts128f(uint32_t a, float x, float y, float z, float w) {
    asm volatile("st.shared.v4.f32 [%0], {%1,%2,%3,%4};" :: "r"(a), "f"(x), "f"(y), "f"(z), "f"(w) : "memory");
}
__device__ __forceinline__ uint4 ld_poll(const uint4* p) {
    uint4 v;
    asm volatile("ld.relaxed.gpu.global.v4.u32 {%0,%1,%2,%3}, [%4];" : "=r"(v.x), "=r"(v.y), "=r"(v.z), "=r"(v.w) : "l"(p) : "memory");
    return v;
}
__device__ __forceinline__ void st_post(uint4* p, uint32_t x, uint32_t y, uint32_t z, uint32_t w) {
    asm volatile("st.relaxed.gpu.global.v4.u32 [%0], {%1,%2,%3,%4};" :: "l"(p), "r"(x), "r"(y), "r"(z), "r"(w) : "memory");
}
__device__ __forceinline__ uint32_t nz(float v) {
    uint32_t u = __float_as_uint(v); return u == 0u ? 0x80000000u : u;
}
__device__ __forceinline__ bool full4(const uint4& v) { return v.x != 0u && v.y != 0u && v.z != 0u && v.w != 0u; }
__device__ __forceinline__ void mma16816(float (&c)[4], uint32_t a0, uint32_t a1, uint32_t a2, uint32_t a3, uint32_t b0, uint32_t b1) {
    asm volatile("mma.sync.aligned.m16n8k16.row.col.f32.bf16.bf16.f32 {%0,%1,%2,%3}, {%4,%5,%6,%7}, {%8,%9}, {%0,%1,%2,%3};"
                 : "+f"(c[0]), "+f"(c[1]), "+f"(c[2]), "+f"(c[3]) : "r"(a0), "r"(a1), "r"(a2), "r"(a3), "r"(b0), "r"(b1));
}
__device__ __forceinline__ uint32_t pack_bf16(float lo, float hi) {
    uint32_t r; asm("cvt.rn.bf16x2.f32 %0, %1, %2;" : "=r"(r) : "f"(hi), "f"(lo)); return r;
}
__device__ __forceinline__ float rbf(float v) { return __bfloat162float(__float2bfloat16_rn(v)); }
__device__ __forceinline__ float bf_lo(uint32_t u) { return __uint_as_float(u << 16); }
__device__ __forceinline__ float bf_hi(uint32_t u) { return __uint_as_float(u & 0xFFFF0000u); }
__device__ __forceinline__ void named_bar(int id, int n) { asm volatile("bar.sync %0, %1;" :: "r"(id), "r"(n) : "memory"); }

__device__ __forceinline__ void gemv_step(float (&c0)[4], float (&c1)[4], const uint4& wa, const uint4& wb,
                                          uint32_t xr, uint32_t sel_lo, uint32_t sel_hi) {
    uint32_t b0 = __byte_perm(xr, 0u, sel_lo), b1 = __byte_perm(xr, 0u, sel_hi);
    mma16816(c0, wa.x, wa.y, wb.x, wb.y, b0, b1);
    mma16816(c1, wa.z, wa.w, wb.z, wb.w, b0, b1);
}

__global__ void __cluster_dims__(2, 1, 1) __launch_bounds__(NTHREADS, 1)
fused_decode_kernel(const __grid_constant__ CUtensorMap map_wq, const __grid_constant__ CUtensorMap map_wo,
                    const __grid_constant__ CUtensorMap map_wg, const __grid_constant__ CUtensorMap map_wu,
                    const __grid_constant__ CUtensorMap map_wd,
                    const __nv_bfloat16* __restrict__ x, const __nv_bfloat16* __restrict__ kc,
                    const __nv_bfloat16* __restrict__ vc,
                    const __nv_bfloat16* __restrict__ gate_w, __nv_bfloat16* __restrict__ out) {
    extern __shared__ __align__(1024) unsigned char smem_raw[];
    const uint32_t sb = (uint32_t)__cvta_generic_to_shared(smem_raw);
    const int warp = threadIdx.x >> 5, lane = threadIdx.x & 31;
    const int g = lane >> 2, t = lane & 3;
    const int cta = blockIdx.x;
    const int s = cta & 1;
    const int cl = cta >> 1;
    const int b = cl & 1, h = cl >> 1;
    auto bar = [&](int i) { return sb + OFF_BAR + 8u * i; };
    const uint32_t sel_lo = (g & 1) ? 0x1044u : 0x4410u;
    const uint32_t sel_hi = (g & 1) ? 0x3244u : 0x4432u;

    if (warp == 7) PROF(0);
    if (threadIdx.x == 8 * 32) {
        uint64_t pol;
        asm volatile("createpolicy.fractional.L2::evict_first.b64 %0, 1.0;" : "=l"(pol));
        const char* kp = (const char*)(kc + ((size_t)(b * NHEAD + h) * SK + (SK - WIN) + s * (WIN / 2)) * DH);
#pragma unroll
        for (int c = 0; c < N0; c++) mbar_init(bar(c), 1);
        asm volatile("fence.proxy.async.shared::cta;" ::: "memory");
#pragma unroll
        for (int i = 0; i < N0; i++) {
            const int c = i < KF ? C_K + i : i < KF + 4 ? i - KF : i;
            mbar_expect(bar(c), CH);
            if (c < C_K) tma3d(sb + i * CH, &map_wq, (c ^ (b * QSWAP)) * 128, h * 2 + s, bar(c));
            else bulk_g2s_stream(sb + i * CH, kp + (c - C_K) * CH, CH, bar(c), pol);
        }
    }
    if (threadIdx.x == 9 * 32) asm volatile("prefetch.tensormap [%0];" :: "l"(&map_wq) : "memory");
    __syncwarp();
    if (warp == 8) PROF(25);
    if (warp < 8) {
        uint32_t xr[8];
#pragma unroll
        for (int i = 0; i < 8; i++) xr[i] = __ldg((const uint32_t*)(x + b * D_MODEL + (warp ^ (b * QSWAP * 2)) * 64 + i * 8 + t * 2));
        asm volatile("barrier.cluster.arrive.relaxed.aligned;" ::: "memory");
        named_bar(0, NTHREADS);
        if (warp == 7) PROF(24);
        mbar_wait(bar(C_WQ + (warp >> 1)));
        if (warp == 7) PROF(23);
        {
            const uint32_t a0 = sb + slot(C_WQ) + (warp * 64 + 2 * t) * 128 + ((g ^ (2 * t)) << 4);
            const uint32_t a1 = (a0 + 128) ^ 16;
            uint4 wa[8], wb[8];
#pragma unroll
            for (int i = 0; i < 8; i++) { wa[i] = lds128(a0 + i * 1024); wb[i] = lds128(a1 + i * 1024); }
            float c0[4] = {0.f, 0.f, 0.f, 0.f}, c1[4] = {0.f, 0.f, 0.f, 0.f};
#pragma unroll
            for (int i = 0; i < 8; i++) gemv_step(c0, c1, wa[i], wb[i], xr[i], sel_lo, sel_hi);
            if (t == 0) {
                const uint32_t a = sb + OFF_QPART + warp * 256 + g * 32;
                sts128f(a, c0[0], c0[1], c0[2], c0[3]);
                sts128f(a + 16, c1[0], c1[1], c1[2], c1[3]);
            }
        }
        named_bar(1, 256);
        if (warp == 1 && lane == 0) mbar_arrive(bar(B_WQFREE));
        if (warp == 0) {
            PROF(1);
            float lo = 0.f, hi = 0.f;
#pragma unroll
            for (int i = 0; i < 8; i++) { float2 v = lds64f(sb + OFF_QPART + i * 256 + lane * 8); lo += v.x; hi += v.y; }
            const uint32_t qq = pack_bf16(lo, hi);
            const uint32_t a = sb + OFF_Q + s * 128 + lane * 4;
            st_async_b32(mapa(a, 0), qq, mapa(bar(B_Q), 0));
            st_async_b32(mapa(a, 1), qq, mapa(bar(B_Q), 1));
        }
        mbar_wait(bar(B_Q));
        if (warp == 0) PROF(2);
        uint4 qf[4];
#pragma unroll
        for (int j = 0; j < 4; j++) qf[j] = lds128(sb + OFF_Q + ((4 * (j ^ (g & 1)) + t) << 4));

        const int wh = warp >> 2;
        float sc[8];
#pragma unroll
        for (int T = 0; T < 4; T++) {
            mbar_wait(bar(C_K + 2 * T + wh));
            if (warp == 7) PROF(3 + T);
            const uint32_t a = sb + (wh ? slot(C_K + 2 * T + 1) : slot(C_K + 2 * T)) + ((warp & 3) * 16 + g) * 256 + t * 16;
            uint4 kg[4], kh[4];
#pragma unroll
            for (int j = 0; j < 4; j++) {
                kg[j] = lds128(a + ((j ^ (g & 1)) << 6));
                kh[j] = lds128(a + 2048 + ((j ^ (g & 1)) << 6));
            }
            float c0[4] = {0.f, 0.f, 0.f, 0.f}, c1[4] = {0.f, 0.f, 0.f, 0.f};
#pragma unroll
            for (int j = 0; j < 4; j++) {
                mma16816(c0, kg[j].x, kh[j].x, kg[j].y, kh[j].y, qf[j].x, qf[j].y);
                mma16816(c1, kg[j].z, kh[j].z, kg[j].w, kh[j].w, qf[j].z, qf[j].w);
            }
            const float s_lo = (g & 1) ? c0[1] + c1[1] : c0[0] + c1[0];
            const float s_hi = (g & 1) ? c0[3] + c1[3] : c0[2] + c1[2];
            sc[2 * T]     = rbf(rbf(s_lo) * 0.08838834764831845f);
            sc[2 * T + 1] = rbf(rbf(s_hi) * 0.08838834764831845f);
            __syncwarp();
            if (lane == 0) mbar_arrive(bar(B_KFREE + 2 * T + wh));
        }
        float m = sc[0];
#pragma unroll
        for (int i = 1; i < 8; i++) m = fmaxf(m, sc[i]);
        m = fmaxf(m, __shfl_xor_sync(0xffffffffu, m, 4));
        m = fmaxf(m, __shfl_xor_sync(0xffffffffu, m, 8));
        m = fmaxf(m, __shfl_xor_sync(0xffffffffu, m, 16));
        uint32_t pe[4], po[4];
        float l = 0.f;
        const float ms = (m == -INFINITY) ? 0.f : m;
#pragma unroll
        for (int T = 0; T < 4; T++) {
            const float p0 = exp2f((sc[2 * T] - ms) * 1.4426950408889634f);
            const float p1 = exp2f((sc[2 * T + 1] - ms) * 1.4426950408889634f);
            l += p0 + p1;
            const uint32_t pp = pack_bf16(p0, p1);
            const uint32_t nb = __shfl_xor_sync(0xffffffffu, pp, 4);
            pe[T] = (g & 1) ? nb : pp;
            po[T] = (g & 1) ? pp : nb;
        }
        l += __shfl_xor_sync(0xffffffffu, l, 4);
        l += __shfl_xor_sync(0xffffffffu, l, 8);
        l += __shfl_xor_sync(0xffffffffu, l, 16);
        if (lane < 2) st_async_v2(mapa(sb + OFF_STAT + (s * 8 + warp) * 8, lane), m, l, mapa(bar(B_STAT), lane));

        const bool diag = (t == (g >> 1));
        const uint32_t dsel_lo = diag ? sel_lo : 0x4444u, dsel_hi = diag ? sel_hi : 0x4444u;
        float acc[4][4];
#pragma unroll
        for (int i = 0; i < 4; i++) { acc[i][0] = acc[i][1] = acc[i][2] = acc[i][3] = 0.f; }
        float fscale = 0.f;
#pragma unroll
        for (int T = 0; T < 4; T++) {
            if (T == 3) {
                mbar_wait(bar(B_STAT));
                const float2 st = lds64f(sb + OFF_STAT + (lane & 15) * 8);
                float M = st.x;
#pragma unroll
                for (int o = 1; o < 16; o <<= 1) M = fmaxf(M, __shfl_xor_sync(0xffffffffu, M, o));
                float L = st.y * exp2f((st.x - M) * 1.4426950408889634f);
#pragma unroll
                for (int o = 1; o < 16; o <<= 1) L += __shfl_xor_sync(0xffffffffu, L, o);
                fscale = exp2f((m - M) * 1.4426950408889634f) / L;
            }
            mbar_wait(bar(C_V + 2 * T + wh));
            if (warp == 7) PROF(7 + T);
            const uint32_t a = sb + (wh ? slot(C_V + 2 * T + 1) : slot(C_V + 2 * T)) + ((warp & 3) * 16 + 2 * t) * 256 + ((g ^ (2 * t)) << 4);
            uint4 va[4], vb[4];
#pragma unroll
            for (int i = 0; i < 4; i++) {
                va[i] = lds128(a + (i >> 1) * 256 + (i & 1) * 128);
                vb[i] = lds128(a + 2048 + (i >> 1) * 256 + (i & 1) * 128);
            }
            gemv_step(acc[0], acc[1], va[0], vb[0], pe[T], dsel_lo, dsel_hi);
            gemv_step(acc[2], acc[3], va[1], vb[1], pe[T], dsel_lo, dsel_hi);
            gemv_step(acc[0], acc[1], va[2], vb[2], po[T], dsel_lo, dsel_hi);
            gemv_step(acc[2], acc[3], va[3], vb[3], po[T], dsel_lo, dsel_hi);
            if (T == 0 && V_REUSED) {
                __syncwarp();
                if (lane == 0) mbar_arrive(bar(B_VFREE + wh));
            }
        }
        {
            float r[8];
#pragma unroll
            for (int i = 0; i < 8; i++) {
                const float lo = acc[i >> 2][i & 3], hi = acc[2 + (i >> 2)][i & 3];
                const float send = (t & 1) ? lo : hi, keep = (t & 1) ? hi : lo;
                r[i] = keep + __shfl_xor_sync(0xffffffffu, send, 9);
            }
            float q4[4];
#pragma unroll
            for (int i = 0; i < 4; i++) {
                const float send = (t & 2) ? r[i] : r[4 + i], keep = (t & 2) ? r[4 + i] : r[i];
                q4[i] = (keep + __shfl_xor_sync(0xffffffffu, send, 18)) * fscale;
            }
            const int dim = (t & 1) * 64 + (g ^ (2 * t)) * 8 + (t >> 1) * 4;
            const uint32_t a = sb + OFF_OPART + (s * 8 + warp) * 512 + dim * 4;
            st_async_v4(mapa(a, 0), q4[0], q4[1], q4[2], q4[3], mapa(bar(B_O), 0));
            st_async_v4(mapa(a, 1), q4[0], q4[1], q4[2], q4[3], mapa(bar(B_O), 1));
        }
        if (warp >= 4) return;
        mbar_wait(bar(B_O));
        if (warp == 0) PROF(11);
        {
            float v[16];
#pragma unroll
            for (int i = 0; i < 16; i++) v[i] = lds32f(sb + OFF_OPART + i * 512 + threadIdx.x * 4);
#pragma unroll
            for (int i = 0; i < 8; i++) v[i] += v[i + 8];
#pragma unroll
            for (int i = 0; i < 4; i++) v[i] += v[i + 4];
            v[0] = (v[0] + v[2]) + (v[1] + v[3]);
            const unsigned short ob = __bfloat16_as_ushort(__float2bfloat16_rn(v[0]));
            const int pos = warp * 32 + ((lane >> 1) & 3) * 8 + (lane >> 3) * 2 + (lane & 1);
            asm volatile("st.shared.u16 [%0], %1;" :: "r"(sb + OFF_O + pos * 2), "h"(ob) : "memory");
        }
        named_bar(2, 128);
        uint4 of[4];
#pragma unroll
        for (int T = 0; T < 4; T++) of[T] = lds128(sb + OFF_O + (T ^ (b * WSWAP)) * 64 + t * 16);
        if (warp == 0) PROF(12);
        float c0[4] = {0.f, 0.f, 0.f, 0.f}, c1[4] = {0.f, 0.f, 0.f, 0.f};
        float c2[4] = {0.f, 0.f, 0.f, 0.f}, c3[4] = {0.f, 0.f, 0.f, 0.f};
#pragma unroll
        for (int T = 0; T < 4; T++) {
            mbar_wait(bar(C_WO + T));
            if (warp == 0) PROF(13 + T);
            const uint32_t a0 = sb + slot(C_WO + T) + warp * 4096 + 2 * t * 128 + ((g ^ (2 * t)) << 4);
            const uint32_t a1 = (a0 + 128) ^ 16;
            uint4 ww[8];
#pragma unroll
            for (int i = 0; i < 4; i++) { ww[2 * i] = lds128(a0 + i * 1024); ww[2 * i + 1] = lds128(a1 + i * 1024); }
            gemv_step(c0, c1, ww[0], ww[1], of[T].x, sel_lo, sel_hi);
            gemv_step(c2, c3, ww[2], ww[3], of[T].y, sel_lo, sel_hi);
            gemv_step(c0, c1, ww[4], ww[5], of[T].z, sel_lo, sel_hi);
            gemv_step(c2, c3, ww[6], ww[7], of[T].w, sel_lo, sel_hi);
        }
        if (t < 2) {
            float r[4];
#pragma unroll
            for (int i = 0; i < 4; i++) r[i] = t ? c1[i] + c3[i] : c0[i] + c2[i];
            const int cg = s * 32 + warp * 8 + g;
            st_post(&g_partA[((b * 64 + cg) * NHEAD + h) * 2 + t], nz(r[0]), nz(r[1]), nz(r[2]), nz(r[3]));
        }
        if (warp == 0) PROF(17);
    } else if (warp == 8) {
        const size_t kvoff = ((size_t)(b * NHEAD + h) * SK + (SK - WIN) + s * (WIN / 2)) * DH;
        const char* kp = (const char*)(kc + kvoff);
        const char* vp = (const char*)(vc + kvoff);
        uint64_t pol;
        asm volatile("createpolicy.fractional.L2::evict_first.b64 %0, 1.0;" : "=l"(pol));
        asm volatile("barrier.cluster.arrive.relaxed.aligned;" ::: "memory");
        const bool ffn = cl < NUNIT;
        const uint32_t e = SchedSel<N0>::get(lane, ffn);
        const int c = e & 255;
        const uint32_t dst = sb + (e >> 24) * CH, mb = bar(c);
        const uint32_t b_land = bar((int)((e >> 8) & 255) - 1), b_free = bar((int)((e >> 16) & 255) - 1);
        const char* src = c < C_V ? kp + (c - C_K) * CH : vp + (c - C_V) * CH;
        const CUtensorMap* map = c < C_K ? &map_wq : c < C_GU ? &map_wo : c == C_WD ? &map_wd : s ? &map_wu : &map_wg;
        const bool linear = c >= C_K && c < C_WO, four = c == C_WD || (c >= C_WO && c < C_GU);
        const int c0 = c < C_K ? h * 2 + s : four ? s * 4 : cl;
        const int c1 = c < C_K ? (c ^ (b * QSWAP)) * 128 : c < C_GU ? h * DH + ((c - C_WO) ^ (b * WSWAP)) * 32
                     : c == C_WD ? cl * 32 : (c - C_GU) * 256;
        named_bar(0, NTHREADS);
        const int nstep = ffn ? C_COUNT : C_GU;
#pragma unroll 1
        for (int n = N0; n < nstep; n++) {
            if (lane == n) {
                if (e & 0xFF0000u) mbar_wait(b_free);
                if (e & 0xFF00u) mbar_wait(b_land);
                mbar_expect(mb, CH);
                if (linear) bulk_g2s_stream(dst, src, CH, mb, pol);
                else tma3d(dst, map, c1, c0, mb);
            }
            __syncwarp();
        }
        PROF(18);
    } else if (warp == 13) {
        if (lane == 0) {
#pragma unroll
            for (int i = N0; i < B_COUNT; i++) mbar_init(bar(i), i >= B_WDFREE ? 4 : 1);
            asm volatile("fence.mbarrier_init.release.cluster;" ::: "memory");
            asm volatile("fence.proxy.async.shared::cta;" ::: "memory");
            mbar_expect(bar(B_Q), 256); mbar_expect(bar(B_STAT), 128); mbar_expect(bar(B_O), 8192); mbar_expect(bar(B_F), 512);
        }
        __syncwarp();
        asm volatile("barrier.cluster.arrive.relaxed.aligned;" ::: "memory");
        asm volatile("barrier.cluster.wait.aligned;" ::: "memory");
        named_bar(0, NTHREADS);
        if (lane == 0) {
            asm volatile("prefetch.tensormap [%0];" :: "l"(s ? &map_wu : &map_wg) : "memory");
            asm volatile("prefetch.tensormap [%0];" :: "l"(&map_wd) : "memory");
            asm volatile("prefetch.tensormap [%0];" :: "l"(&map_wo) : "memory");
        }
        const int rb = cta >> 6;
        const uint4 x0 = ldg128(x + rb * D_MODEL + lane * 16), x1 = ldg128(x + rb * D_MODEL + lane * 16 + 8);
        const uint4 g0 = ldg128(gate_w + lane * 16), g1 = ldg128(gate_w + lane * 16 + 8);
        float gate;
        {
            const uint32_t xv[8] = {x0.x, x0.y, x0.z, x0.w, x1.x, x1.y, x1.z, x1.w};
            const uint32_t gv[8] = {g0.x, g0.y, g0.z, g0.w, g1.x, g1.y, g1.z, g1.w};
            float z = 0.f;
#pragma unroll
            for (int i = 0; i < 8; i++) z += rbf(bf_lo(xv[i]) * bf_lo(gv[i])) + rbf(bf_hi(xv[i]) * bf_hi(gv[i]));
#pragma unroll
            for (int o = 16; o > 0; o >>= 1) z += __shfl_xor_sync(0xffffffffu, z, o);
            z = rbf(z);
            gate = rbf(1.f / (1.f + __expf(-z)));
        }
        const float mix = (lane & 2) ? gate : rbf(1.f - gate);
        uint4* pf = g_partF + cta * (NUNIT * 2) + lane;
        uint4* pa = g_partA + cta * (NHEAD * 2) + lane;
        const bool has3 = lane < NUNIT * 2 - 64;
        const uint32_t e3 = has3 ? 0u : 0x80000000u;
        uint4 f0 = make_uint4(0u, 0u, 0u, 0u), f1 = f0, a0 = f0, a1 = f0, f2 = make_uint4(e3, e3, e3, e3);
        mbar_wait(bar(C_V + 7));
        int it = 0;
        while (!mbar_test(bar(C_WO + 3)) && ++it < SPIN_LIMIT) {
            if (!full4(f0)) f0 = ld_poll(pf);
            if (!full4(f1)) f1 = ld_poll(pf + 32);
            if (!full4(f2)) f2 = ld_poll(pf + 64);
            if (__all_sync(0xffffffffu, full4(f0) && full4(f1) && full4(f2))) break;
        }
        PROF(19);
        mbar_wait(bar(C_WO + 3));
        it = 0;
        do {
            if (!full4(a0)) a0 = ld_poll(pa);
            if (!full4(a1)) a1 = ld_poll(pa + 32);
            if (!full4(f0)) f0 = ld_poll(pf);
            if (!full4(f1)) f1 = ld_poll(pf + 32);
            if (!full4(f2)) f2 = ld_poll(pf + 64);
        } while (!__all_sync(0xffffffffu, full4(a0) && full4(a1) && full4(f0) && full4(f1) && full4(f2)) && ++it < SPIN_LIMIT);
        PROF(20);
        {
            float fa[4], fb[4], r[4];
            fa[0] = __uint_as_float(a0.x) + __uint_as_float(a1.x);
            fa[1] = __uint_as_float(a0.y) + __uint_as_float(a1.y);
            fa[2] = __uint_as_float(a0.z) + __uint_as_float(a1.z);
            fa[3] = __uint_as_float(a0.w) + __uint_as_float(a1.w);
            fb[0] = __uint_as_float(f0.x) + __uint_as_float(f1.x) + __uint_as_float(f2.x);
            fb[1] = __uint_as_float(f0.y) + __uint_as_float(f1.y) + __uint_as_float(f2.y);
            fb[2] = __uint_as_float(f0.z) + __uint_as_float(f1.z) + __uint_as_float(f2.z);
            fb[3] = __uint_as_float(f0.w) + __uint_as_float(f1.w) + __uint_as_float(f2.w);
#pragma unroll
            for (int i = 0; i < 4; i++)
                r[i] = ((lane & 2) ? fa[i] : fb[i]) + __shfl_xor_sync(0xffffffffu, (lane & 2) ? fb[i] : fa[i], 2);
#pragma unroll
            for (int i = 0; i < 2; i++)
                r[i] = ((lane & 4) ? r[2 + i] : r[i]) + __shfl_xor_sync(0xffffffffu, (lane & 4) ? r[i] : r[2 + i], 4);
            r[0] = ((lane & 8) ? r[1] : r[0]) + __shfl_xor_sync(0xffffffffu, (lane & 8) ? r[0] : r[1], 8);
            r[0] += __shfl_xor_sync(0xffffffffu, r[0], 16);
            r[0] = rbf(mix * rbf(r[0]));
            r[0] += __shfl_xor_sync(0xffffffffu, r[0], 2);
            if ((lane & 18) == 0)
                out[cta * 8 + (lane & 1) * 4 + ((lane >> 1) & 2) + (lane >> 3)] = __float2bfloat16_rn(r[0]);
        }
        st_post(pa, 0u, 0u, 0u, 0u); st_post(pa + 32, 0u, 0u, 0u, 0u);
        st_post(pf, 0u, 0u, 0u, 0u); st_post(pf + 32, 0u, 0u, 0u, 0u);
        if (has3) st_post(pf + 64, 0u, 0u, 0u, 0u);
        PROF(21);
    } else {
        asm volatile("barrier.cluster.arrive.relaxed.aligned;" ::: "memory");
        const int fw = warp - 9;
        const int row0 = fw * 128 + (g >> 2) * 64 + (t >> 1) * 4;
        uint2 xw[8];
#pragma unroll
        for (int i = 0; i < 8; i++) xw[i] = __ldg((const uint2*)(x + ((g >> 1) & 1) * D_MODEL + row0 + i * 8));
        named_bar(0, NTHREADS);
        if (cl >= NUNIT) return;
        mbar_wait(bar(C_GU + (fw >> 1)));
        {
            const uint32_t a0 = sb + ((fw >> 1) ? slot(C_GU + 1) : slot(C_GU)) + ((row0 & 255) + (t & 1)) * 64 + (((g & 3) ^ (t & 2)) << 4);
            const uint32_t a1 = (a0 + 128) ^ 16;
            uint4 wa[8], wb[8];
#pragma unroll
            for (int i = 0; i < 8; i++) { wa[i] = lds128(a0 + i * 512); wb[i] = lds128(a1 + i * 512); }
            const uint32_t sel = (t & 1) ? 0x7632u : 0x5410u;
            float c0[4] = {0.f, 0.f, 0.f, 0.f}, c1[4] = {0.f, 0.f, 0.f, 0.f};
#pragma unroll
            for (int i = 0; i < 8; i++) gemv_step(c0, c1, wa[i], wb[i], __byte_perm(xw[i].x, xw[i].y, sel), sel_lo, sel_hi);
            if ((t >> 1) == (g >> 2)) {
                const uint32_t a = sb + OFF_FPART + (fw * 2 + (g >> 2)) * 256 + (t & 1) * 128 + (g & 3) * 32;
                sts128f(a, c0[0], c0[1], c0[2], c0[3]);
                sts128f(a + 16, c1[0], c1[1], c1[2], c1[3]);
            }
        }
        named_bar(3, 128);
        if (fw == 1 && lane == 0) mbar_arrive(bar(B_GUFREE));
        if (fw == 0) {
            float lo = 0.f, hi = 0.f;
#pragma unroll
            for (int i = 0; i < 8; i++) { float2 v = lds64f(sb + OFF_FPART + i * 256 + lane * 8); lo += v.x; hi += v.y; }
            lo = rbf(lo); hi = rbf(hi);
            const uint32_t a = sb + OFF_GU + s * 256 + lane * 8;
            st_async_v2(mapa(a, 0), lo, hi, mapa(bar(B_F), 0));
            st_async_v2(mapa(a, 1), lo, hi, mapa(bar(B_F), 1));
        }
        mbar_wait(bar(B_F));
        {
            const uint32_t a = sb + OFF_GU + ((g >> 1) & 1) * 128 + t * 8;
            uint32_t hh[4];
#pragma unroll
            for (int i = 0; i < 4; i++) {
                const float2 gv = lds64f(a + i * 32), uv = lds64f(a + 256 + i * 32);
                hh[i] = pack_bf16(gv.x * uv.x, gv.y * uv.y);
            }
            mbar_wait(bar(C_WD));
            const uint32_t a0 = sb + slot(C_WD) + fw * 4096 + 2 * t * 128 + ((g ^ (2 * t)) << 4);
            const uint32_t a1 = (a0 + 128) ^ 16;
            float c0[4] = {0.f, 0.f, 0.f, 0.f}, c1[4] = {0.f, 0.f, 0.f, 0.f};
#pragma unroll
            for (int i = 0; i < 4; i++) {
                const uint4 wa = lds128(a0 + i * 1024), wb = lds128(a1 + i * 1024);
                gemv_step(c0, c1, wa, wb, hh[i], sel_lo, sel_hi);
            }
            if (WD_REUSED) {
                __syncwarp();
                if (lane == 0) mbar_arrive(bar(B_WDFREE));
            }
            float r[4];
#pragma unroll
            for (int i = 0; i < 4; i++) r[i] = (t >> 1) ? c1[i] : c0[i];
            const int cg = s * 32 + fw * 8 + g;
            st_post(&g_partF[(((t & 1) * 64 + cg) * NUNIT + cl) * 2 + (t >> 1)], nz(r[0]), nz(r[1]), nz(r[2]), nz(r[3]));
        }
        if (fw == 0) PROF(22);
    }
}

}

typedef CUresult (*EncodeFn)(CUtensorMap*, CUtensorMapDataType, cuuint32_t, void*, const cuuint64_t*, const cuuint64_t*,
                             const cuuint32_t*, const cuuint32_t*, CUtensorMapInterleave, CUtensorMapSwizzle,
                             CUtensorMapL2promotion, CUtensorMapFloatOOBfill);

static void make_map(EncodeFn enc, CUtensorMap* m, void* base, uint64_t cols, uint64_t rows,
                     uint32_t box_cols, uint32_t box_rows, uint32_t box_blks) {
    const cuuint64_t dims[3] = {box_cols, rows, cols / box_cols};
    const cuuint64_t strides[2] = {cols * 2, (uint64_t)box_cols * 2};
    const cuuint32_t box[3] = {box_cols, box_rows, box_blks};
    const cuuint32_t es[3] = {1, 1, 1};
    CUresult r = enc(m, CU_TENSOR_MAP_DATA_TYPE_BFLOAT16, 3, base, dims, strides, box, es, CU_TENSOR_MAP_INTERLEAVE_NONE,
        box_cols == 64 ? CU_TENSOR_MAP_SWIZZLE_128B : CU_TENSOR_MAP_SWIZZLE_64B, PROMO, CU_TENSOR_MAP_FLOAT_OOB_FILL_NONE);
    (void)r;
}

extern "C" void kernel_launch(void* const* d_in, const int* in_sizes, int n_in, void* d_out, int out_size) {
    (void)in_sizes; (void)n_in; (void)out_size;
    static EncodeFn enc = nullptr;
    if (!enc) {
        cudaFuncSetAttribute(fused_decode_kernel, cudaFuncAttributeMaxDynamicSharedMemorySize, (int)SMEM_BYTES);
        void* fn = nullptr;
        cudaDriverEntryPointQueryResult qr;
        cudaGetDriverEntryPoint("cuTensorMapEncodeTiled", &fn, cudaEnableDefault, &qr);
        enc = (EncodeFn)fn;
    }
    CUtensorMap map_wq, map_wo, map_wg, map_wu, map_wd;
    make_map(enc, &map_wq, d_in[3], NHEAD * DH, D_MODEL, 64, 128, 1);
    make_map(enc, &map_wo, d_in[4], D_MODEL, NHEAD * DH, 64, 32, 4);
    make_map(enc, &map_wg, d_in[6], FF, D_MODEL, 32, 256, 1);
    make_map(enc, &map_wu, d_in[7], FF, D_MODEL, 32, 256, 1);
    make_map(enc, &map_wd, d_in[8], D_MODEL, FF, 64, 32, 4);
    typedef const __nv_bfloat16* P;
    fused_decode_kernel<<<NCTA, NTHREADS, SMEM_BYTES>>>(map_wq, map_wo, map_wg, map_wu, map_wd, (P)d_in[0], (P)d_in[1],
                                                        (P)d_in[2], (P)d_in[9], (__nv_bfloat16*)d_out);
}
```

```cpp
#include <cuda_runtime.h>
#include <cuda.h>
#include <cuda_bf16.h>
#include <stdint.h>
#include <type_traits>

namespace {

constexpr int D_MODEL = 512;
constexpr int NHEAD   = 32;
constexpr int SK      = 4096;
constexpr int DH      = 128;
constexpr int WIN     = 1024;
constexpr int FF      = 1376;
constexpr int NUNIT   = FF / 32;
constexpr int NCTA    = 128;
constexpr int NTHREADS = 14 * 32;

constexpr uint32_t CH = 16384;
enum { C_WQ = 0, C_K = 4, C_V = 12, C_WO = 20, C_GU = 24, C_WD = 26, C_COUNT = 27 };
#define P0 7
#define P1 11
#define P2 16
#define WT_FFN 0
#define ORDER 4
#define PFM 1
#define KF 2
__host__ __device__ constexpr int chunk_at(int i) {
    if (i < KF) return C_K + i;
    if (i < KF + 4) return C_WQ + i - KF;
    return i == P0 ? C_GU : i == P1 ? C_GU + 1 : i == P2 ? C_WD : i - (i > P0) - (i > P1) - (i > P2);
}
__host__ __device__ constexpr int pos_of(int c) { int i = 0; while (chunk_at(i) != c) i++; return i; }
__host__ __device__ constexpr unsigned long long slot_tab(int c0) {
    unsigned long long v = 0;
    for (int c = c0; c < c0 + 16 && c < C_COUNT; c++) v |= (unsigned long long)(pos_of(c) % 13) << (4 * (c - c0));
    return v;
}
constexpr unsigned long long SLOT_LO = slot_tab(0), SLOT_HI = slot_tab(16);
constexpr bool V_REUSED = pos_of(C_V) + 13 < C_COUNT, WD_REUSED = pos_of(C_WD) + 13 < C_COUNT;
__host__ __device__ constexpr uint32_t slot(int c) { return (uint32_t)(((c < 16 ? SLOT_LO : SLOT_HI) >> (4 * (c & 15))) & 15) * CH; }
#define WT_WQ 0
#define WT_WO 1
__host__ __device__ constexpr int chunk_wt(int c) { return c < C_K ? WT_WQ : (c >= C_WO && c < C_GU) ? WT_WO : c >= C_GU ? WT_FFN : 2; }
constexpr uint32_t OFF_MISC = 13 * CH;
constexpr uint32_t OFF_OPART = OFF_MISC;
constexpr uint32_t OFF_QPART = OFF_OPART + 8192;
constexpr uint32_t OFF_FPART = OFF_QPART + 2048;
constexpr uint32_t OFF_GU    = OFF_FPART + 2048;
constexpr uint32_t OFF_Q     = OFF_GU + 512;
constexpr uint32_t OFF_O     = OFF_Q + 256;
constexpr uint32_t OFF_STAT  = OFF_O + 256;
constexpr uint32_t OFF_BAR   = OFF_STAT + 128;
constexpr uint32_t SMEM_BYTES = OFF_BAR + 512;
enum { B_Q = C_COUNT, B_STAT, B_O, B_F, B_INIT, B_WQFREE, B_GUFREE, B_WDFREE, B_KFREE, B_VFREE = B_KFREE + 8, B_COUNT = B_VFREE + 2 };
#define WIN_F 12
#define WIN_END WIN_F
#define WIN_0 6
#define WIN_N 12
#define QSWAP 0
#define PROMO CU_TENSOR_MAP_L2_PROMOTION_NONE
#define WSWAP 0
#define OOO 1
#define PACE 1
#define WIN_LO 4
#define PACE_T0 -1400
#define PACE_D 650
struct Sched { uint32_t e[32], d[32]; int n, n0; };
__host__ __device__ constexpr Sched make_sched(bool ffn) {
    Sched S{}; int hist[C_COUNT] = {}; int n = 0, landed = 0, infl = 0, cum = 0; S.n0 = -1;
    for (int i = 0; i < C_COUNT; i++) {
        const int c = chunk_at(i);
        cum += c >= C_GU ? 672 : c >= C_K && c < C_WO ? 1000 : 500;
        if (!ffn && c >= C_GU) continue;
        const int W = (c >= C_WO && c < C_GU) ? WIN_END : S.n0 < 0 ? WIN_0 : ffn ? WIN_F : WIN_N;
        int land = -1, fr = -1;
        infl += chunk_wt(c);
        while (infl > W && landed < n) { land = hist[landed++]; infl -= chunk_wt(land); }
        if (i >= 13) {
            int pc = chunk_at(i - 13);
            if (!ffn && pc >= C_GU) pc = i >= 26 ? chunk_at(i - 26) : -1;
            if (pc >= 0) fr = pc < C_K ? B_WQFREE : pc < C_V ? B_KFREE + pc - C_K : pc < C_WO ? B_VFREE + pc - C_V
                            : pc < C_WD ? B_GUFREE : B_WDFREE;
        }
        if (S.n0 < 0 && (land >= 0 || fr >= 0 || c >= C_V)) S.n0 = n;
        S.e[n] = (uint32_t)c | (uint32_t)(land + 1) << 8 | (uint32_t)(fr + 1) << 16 | (uint32_t)(i % 13) << 24;
        const int dl = PACE_T0 + cum * PACE_D / 1000;
        S.d[n] = (uint32_t)chunk_wt(c) | (uint32_t)W << 4 | (uint32_t)(dl < 0 ? 0 : dl) << 12;
        hist[n++] = c;
    }
    S.n = n;
    return S;
}
constexpr int N0 = make_sched(true).n0 < make_sched(false).n0 ? make_sched(true).n0 : make_sched(false).n0;
static_assert(N0 >= KF + 4, "initial burst covers wq");
template <int I> struct SchedSel {
    static __device__ __forceinline__ uint2 get(int lane, bool ffn) {
        constexpr uint32_t ef = make_sched(true).e[I], en = make_sched(false).e[I];
        constexpr uint32_t df = make_sched(true).d[I], dn = make_sched(false).d[I];
        const uint2 rest = SchedSel<I + 1>::get(lane, ffn);
        return make_uint2(lane == I ? (ffn ? ef : en) : rest.x, lane == I ? (ffn ? df : dn) : rest.y);
    }
};
template <> struct SchedSel<C_COUNT> { static __device__ __forceinline__ uint2 get(int, bool) { return make_uint2(0u, 0u); } };

constexpr int SPIN_LIMIT = 1 << 20;

__device__ uint4 g_partA[NCTA * NHEAD * 2];
__device__ uint4 g_partF[NCTA * NUNIT * 2];
__device__ uint32_t g_cleared;
#define NPOLL 1
#define POLL_GAP 150
#define NPRE 2
#define FPOLL_AT 5

#define PROF(ev) do {} while (0)

__device__ __forceinline__ void mbar_init(uint32_t a, uint32_t c) {
    asm volatile("mbarrier.init.shared::cta.b64 [%0], %1;" :: "r"(a), "r"(c) : "memory");
}
__device__ __forceinline__ void mbar_expect(uint32_t a, uint32_t bytes) {
    asm volatile("mbarrier.arrive.expect_tx.shared::cta.b64 _, [%0], %1;" :: "r"(a), "r"(bytes) : "memory");
}
__device__ __forceinline__ void mbar_arrive(uint32_t a) {
    asm volatile("mbarrier.arrive.shared::cta.b64 _, [%0];" :: "r"(a) : "memory");
}
__device__ __forceinline__ void mbar_wait(uint32_t a) {
    uint32_t ok; int it = 0;
    do {
        asm volatile("{.reg .pred p; mbarrier.try_wait.parity.shared::cta.b64 p, [%1], 0; selp.u32 %0, 1, 0, p;}"
                     : "=r"(ok) : "r"(a) : "memory");
    } while (!ok && ++it < SPIN_LIMIT);
}
__device__ __forceinline__ uint32_t now_ns() { uint32_t t; asm volatile("mov.u32 %0, %globaltimer_lo;" : "=r"(t)); return t; }
__device__ __forceinline__ bool mbar_test(uint32_t a) {
    uint32_t ok;
    asm volatile("{.reg .pred p; mbarrier.test_wait.parity.shared::cta.b64 p, [%1], 0; selp.u32 %0, 1, 0, p;}"
                 : "=r"(ok) : "r"(a) : "memory");
    return ok != 0;
}
__device__ __forceinline__ void bulk_g2s_stream(uint32_t dst, const void* src, uint32_t bytes, uint32_t mbar, uint64_t pol) {
    asm volatile("cp.async.bulk.shared::cluster.global.mbarrier::complete_tx::bytes.L2::cache_hint [%0], [%1], %2, [%3], %4;"
                 :: "r"(dst), "l"(src), "r"(bytes), "r"(mbar), "l"(pol) : "memory");
}
__device__ __forceinline__ void tma3d(uint32_t dst, const CUtensorMap* map, int row, int blk, uint32_t mbar) {
    asm volatile("cp.async.bulk.tensor.3d.shared::cluster.global.mbarrier::complete_tx::bytes [%0], [%1, {%5, %2, %3}], [%4];"
                 :: "r"(dst), "l"(map), "r"(row), "r"(blk), "r"(mbar), "r"(0) : "memory");
}
__device__ __forceinline__ uint32_t mapa(uint32_t a, uint32_t rank) {
    uint32_t r; asm("mapa.shared::cluster.u32 %0, %1, %2;" : "=r"(r) : "r"(a), "r"(rank)); return r;
}
__device__ __forceinline__ void st_async_b32(uint32_t a, uint32_t v, uint32_t mbar) {
    asm volatile("st.async.shared::cluster.mbarrier::complete_tx::bytes.b32 [%0], %1, [%2];" :: "r"(a), "r"(v), "r"(mbar) : "memory");
}
__device__ __forceinline__ void st_async_v2(uint32_t a, float x, float y, uint32_t mbar) {
    asm volatile("st.async.shared::cluster.mbarrier::complete_tx::bytes.v2.f32 [%0], {%1, %2}, [%3];" :: "r"(a), "f"(x), "f"(y), "r"(mbar) : "memory");
}
__device__ __forceinline__ void st_async_v4(uint32_t a, float x, float y, float z, float w, uint32_t mbar) {
    asm volatile("st.async.shared::cluster.mbarrier::complete_tx::bytes.v4.f32 [%0], {%1, %2, %3, %4}, [%5];"
                 :: "r"(a), "f"(x), "f"(y), "f"(z), "f"(w), "r"(mbar) : "memory");
}
__device__ __forceinline__ uint4 ldg128(const void* p) {
    uint4 v;
    asm volatile("ld.global.nc.L1::no_allocate.v4.u32 {%0,%1,%2,%3}, [%4];" : "=r"(v.x), "=r"(v.y), "=r"(v.z), "=r"(v.w) : "l"(p));
    return v;
}
__device__ __forceinline__ uint4 lds128(uint32_t a) {
    uint4 v;
    asm volatile("ld.shared.v4.u32 {%0,%1,%2,%3}, [%4];" : "=r"(v.x), "=r"(v.y), "=r"(v.z), "=r"(v.w) : "r"(a) : "memory");
    return v;
}
__device__ __forceinline__ float lds32f(uint32_t a) {
    float v; asm volatile("ld.shared.f32 %0, [%1];" : "=f"(v) : "r"(a) : "memory"); return v;
}
__device__ __forceinline__ float2 lds64f(uint32_t a) {
    float2 v; asm volatile("ld.shared.v2.f32 {%0,%1}, [%2];" : "=f"(v.x), "=f"(v.y) : "r"(a) : "memory"); return v;
}
__device__ __forceinline__ void sts128f(uint32_t a, float x, float y, float z, float w) {
    asm volatile("st.shared.v4.f32 [%0], {%1,%2,%3,%4};" :: "r"(a), "f"(x), "f"(y), "f"(z), "f"(w) : "memory");
}
__device__ __forceinline__ uint4 ld_poll(const uint4* p) {
    uint4 v;
    asm volatile("ld.relaxed.gpu.global.v4.u32 {%0,%1,%2,%3}, [%4];" : "=r"(v.x), "=r"(v.y), "=r"(v.z), "=r"(v.w) : "l"(p) : "memory");
    return v;
}
__device__ __forceinline__ bool full4(const uint4& v) { return v.x != 0u && v.y != 0u && v.z != 0u && v.w != 0u; }
__device__ __forceinline__ void ld_poll_if(uint4& v, const uint4* p, bool full) {
    asm volatile("{.reg .pred q; setp.eq.u32 q, %5, 0; @q ld.relaxed.gpu.global.v4.u32 {%0,%1,%2,%3}, [%4];}"
                 : "+r"(v.x), "+r"(v.y), "+r"(v.z), "+r"(v.w) : "l"(p), "r"((uint32_t)full) : "memory");
}
__device__ __forceinline__ void st_post(uint4* p, uint32_t x, uint32_t y, uint32_t z, uint32_t w) {
    asm volatile("st.relaxed.gpu.global.v4.u32 [%0], {%1,%2,%3,%4};" :: "l"(p), "r"(x), "r"(y), "r"(z), "r"(w) : "memory");
}
__device__ __forceinline__ uint32_t nz(float v) {
    uint32_t u = __float_as_uint(v); return u == 0u ? 0x80000000u : u;
}
__device__ __forceinline__ void mma16816(float (&c)[4], uint32_t a0, uint32_t a1, uint32_t a2, uint32_t a3, uint32_t b0, uint32_t b1) {
    asm volatile("mma.sync.aligned.m16n8k16.row.col.f32.bf16.bf16.f32 {%0,%1,%2,%3}, {%4,%5,%6,%7}, {%8,%9}, {%0,%1,%2,%3};"
                 : "+f"(c[0]), "+f"(c[1]), "+f"(c[2]), "+f"(c[3]) : "r"(a0), "r"(a1), "r"(a2), "r"(a3), "r"(b0), "r"(b1));
}
__device__ __forceinline__ uint32_t pack_bf16(float lo, float hi) {
    uint32_t r; asm("cvt.rn.bf16x2.f32 %0, %1, %2;" : "=r"(r) : "f"(hi), "f"(lo)); return r;
}
__device__ __forceinline__ float rbf(float v) { return __bfloat162float(__float2bfloat16_rn(v)); }
__device__ __forceinline__ float bf_lo(uint32_t u) { return __uint_as_float(u << 16); }
__device__ __forceinline__ float bf_hi(uint32_t u) { return __uint_as_float(u & 0xFFFF0000u); }
__device__ __forceinline__ void named_bar(int id, int n) { asm volatile("bar.sync %0, %1;" :: "r"(id), "r"(n) : "memory"); }

__device__ __forceinline__ void gemv_step(float (&c0)[4], float (&c1)[4], const uint4& wa, const uint4& wb,
                                          uint32_t xr, uint32_t sel_lo, uint32_t sel_hi) {
    uint32_t b0 = __byte_perm(xr, 0u, sel_lo), b1 = __byte_perm(xr, 0u, sel_hi);
    mma16816(c0, wa.x, wa.y, wb.x, wb.y, b0, b1);
    mma16816(c1, wa.z, wa.w, wb.z, wb.w, b0, b1);
}

__global__ void __cluster_dims__(2, 1, 1) __launch_bounds__(NTHREADS, 1)
fused_decode_kernel(const __grid_constant__ CUtensorMap map_wq, const __grid_constant__ CUtensorMap map_wo,
                    const __grid_constant__ CUtensorMap map_wg, const __grid_constant__ CUtensorMap map_wu,
                    const __grid_constant__ CUtensorMap map_wd,
                    const __nv_bfloat16* __restrict__ x, const __nv_bfloat16* __restrict__ kc,
                    const __nv_bfloat16* __restrict__ vc,
                    const __nv_bfloat16* __restrict__ gate_w, __nv_bfloat16* __restrict__ out) {
    extern __shared__ __align__(1024) unsigned char smem_raw[];
    const uint32_t sb = (uint32_t)__cvta_generic_to_shared(smem_raw);
    const int warp = threadIdx.x >> 5, lane = threadIdx.x & 31;
    const int g = lane >> 2, t = lane & 3;
    const int cta = blockIdx.x;
    const int s = cta & 1;
    const int cl = cta >> 1;
    const int b = cl & 1, h = cl >> 1;
    auto bar = [&](int i) { return sb + OFF_BAR + 8u * i; };
    const uint32_t sel_lo = (g & 1) ? 0x1044u : 0x4410u;
    const uint32_t sel_hi = (g & 1) ? 0x3244u : 0x4432u;

    if (warp == 7) PROF(0);
    if (threadIdx.x == 8 * 32) {
        uint64_t pol;
        asm volatile("createpolicy.fractional.L2::evict_first.b64 %0, 1.0;" : "=l"(pol));
        const char* kp = (const char*)(kc + ((size_t)(b * NHEAD + h) * SK + (SK - WIN) + s * (WIN / 2)) * DH);
#pragma unroll
        for (int c = 0; c < N0; c++) mbar_init(bar(c), 1);
        asm volatile("fence.proxy.async.shared::cta;" ::: "memory");
#pragma unroll
        for (int i = 0; i < N0; i++) {
            const int c = i < KF ? C_K + i : i < KF + 4 ? i - KF : i;
            mbar_expect(bar(c), CH);
            if (c < C_K) tma3d(sb + i * CH, &map_wq, (c ^ (b * QSWAP)) * 128, h * 2 + s, bar(c));
            else bulk_g2s_stream(sb + i * CH, kp + (c - C_K) * CH, CH, bar(c), pol);
        }
    }
    if (threadIdx.x == 9 * 32) asm volatile("prefetch.tensormap [%0];" :: "l"(&map_wq) : "memory");
    __syncwarp();
    if (warp == 8) PROF(25);
    if (warp < 8) {
        uint32_t xr[8];
#pragma unroll
        for (int i = 0; i < 8; i++) xr[i] = __ldg((const uint32_t*)(x + b * D_MODEL + (warp ^ (b * QSWAP * 2)) * 64 + i * 8 + t * 2));
        asm volatile("barrier.cluster.arrive.relaxed.aligned;" ::: "memory");
        named_bar(0, NTHREADS);
        if (warp == 7) PROF(24);
        mbar_wait(bar(C_WQ + (warp >> 1)));
        if (warp == 7) PROF(23);
        {
            const uint32_t a0 = sb + slot(C_WQ) + (warp * 64 + 2 * t) * 128 + ((g ^ (2 * t)) << 4);
            const uint32_t a1 = (a0 + 128) ^ 16;
            uint4 wa[8], wb[8];
#pragma unroll
            for (int i = 0; i < 8; i++) { wa[i] = lds128(a0 + i * 1024); wb[i] = lds128(a1 + i * 1024); }
            float c0[4] = {0.f, 0.f, 0.f, 0.f}, c1[4] = {0.f, 0.f, 0.f, 0.f};
#pragma unroll
            for (int i = 0; i < 8; i++) gemv_step(c0, c1, wa[i], wb[i], xr[i], sel_lo, sel_hi);
            if (t == 0) {
                const uint32_t a = sb + OFF_QPART + warp * 256 + g * 32;
                sts128f(a, c0[0], c0[1], c0[2], c0[3]);
                sts128f(a + 16, c1[0], c1[1], c1[2], c1[3]);
            }
        }
        named_bar(1, 256);
        if (warp == 1 && lane == 0) mbar_arrive(bar(B_WQFREE));
        if (warp == 0) {
            PROF(1);
            float lo = 0.f, hi = 0.f;
#pragma unroll
            for (int i = 0; i < 8; i++) { float2 v = lds64f(sb + OFF_QPART + i * 256 + lane * 8); lo += v.x; hi += v.y; }
            const uint32_t qq = pack_bf16(lo, hi);
            const uint32_t a = sb + OFF_Q + s * 128 + lane * 4;
            st_async_b32(mapa(a, 0), qq, mapa(bar(B_Q), 0));
            st_async_b32(mapa(a, 1), qq, mapa(bar(B_Q), 1));
        }
        mbar_wait(bar(B_Q));
        if (warp == 0) PROF(2);
        uint4 qf[4];
#pragma unroll
        for (int j = 0; j < 4; j++) qf[j] = lds128(sb + OFF_Q + ((4 * (j ^ (g & 1)) + t) << 4));

        const int wh = warp >> 2;
        float sc[8];
#pragma unroll
        for (int T = 0; T < 4; T++) {
            mbar_wait(bar(C_K + 2 * T + wh));
            if (warp == 7) PROF(3 + T);
            const uint32_t a = sb + (wh ? slot(C_K + 2 * T + 1) : slot(C_K + 2 * T)) + ((warp & 3) * 16 + g) * 256 + t * 16;
            uint4 kg[4], kh[4];
#pragma unroll
            for (int j = 0; j < 4; j++) {
                kg[j] = lds128(a + ((j ^ (g & 1)) << 6));
                kh[j] = lds128(a + 2048 + ((j ^ (g & 1)) << 6));
            }
            float c0[4] = {0.f, 0.f, 0.f, 0.f}, c1[4] = {0.f, 0.f, 0.f, 0.f};
#pragma unroll
            for (int j = 0; j < 4; j++) {
                mma16816(c0, kg[j].x, kh[j].x, kg[j].y, kh[j].y, qf[j].x, qf[j].y);
                mma16816(c1, kg[j].z, kh[j].z, kg[j].w, kh[j].w, qf[j].z, qf[j].w);
            }
            const float s_lo = (g & 1) ? c0[1] + c1[1] : c0[0] + c1[0];
            const float s_hi = (g & 1) ? c0[3] + c1[3] : c0[2] + c1[2];
            sc[2 * T]     = rbf(rbf(s_lo) * 0.08838834764831845f);
            sc[2 * T + 1] = rbf(rbf(s_hi) * 0.08838834764831845f);
            __syncwarp();
            if (lane == 0) mbar_arrive(bar(B_KFREE + 2 * T + wh));
        }
        float m = sc[0];
#pragma unroll
        for (int i = 1; i < 8; i++) m = fmaxf(m, sc[i]);
        m = fmaxf(m, __shfl_xor_sync(0xffffffffu, m, 4));
        m = fmaxf(m, __shfl_xor_sync(0xffffffffu, m, 8));
        m = fmaxf(m, __shfl_xor_sync(0xffffffffu, m, 16));
        uint32_t pe[4], po[4];
        float l = 0.f;
        const float ms = (m == -INFINITY) ? 0.f : m;
#pragma unroll
        for (int T = 0; T < 4; T++) {
            const float p0 = exp2f((sc[2 * T] - ms) * 1.4426950408889634f);
            const float p1 = exp2f((sc[2 * T + 1] - ms) * 1.4426950408889634f);
            l += p0 + p1;
            const uint32_t pp = pack_bf16(p0, p1);
            const uint32_t nb = __shfl_xor_sync(0xffffffffu, pp, 4);
            pe[T] = (g & 1) ? nb : pp;
            po[T] = (g & 1) ? pp : nb;
        }
        l += __shfl_xor_sync(0xffffffffu, l, 4);
        l += __shfl_xor_sync(0xffffffffu, l, 8);
        l += __shfl_xor_sync(0xffffffffu, l, 16);
        if (lane < 2) st_async_v2(mapa(sb + OFF_STAT + (s * 8 + warp) * 8, lane), m, l, mapa(bar(B_STAT), lane));

        const bool diag = (t == (g >> 1));
        const uint32_t dsel_lo = diag ? sel_lo : 0x4444u, dsel_hi = diag ? sel_hi : 0x4444u;
        float acc[4][4];
#pragma unroll
        for (int i = 0; i < 4; i++) { acc[i][0] = acc[i][1] = acc[i][2] = acc[i][3] = 0.f; }
        float fscale = 0.f;
#pragma unroll
        for (int T = 0; T < 4; T++) {
            if (T == 3) {
                mbar_wait(bar(B_STAT));
                const float2 st = lds64f(sb + OFF_STAT + (lane & 15) * 8);
                float M = st.x;
#pragma unroll
                for (int o = 1; o < 16; o <<= 1) M = fmaxf(M, __shfl_xor_sync(0xffffffffu, M, o));
                float L = st.y * exp2f((st.x - M) * 1.4426950408889634f);
#pragma unroll
                for (int o = 1; o < 16; o <<= 1) L += __shfl_xor_sync(0xffffffffu, L, o);
                fscale = exp2f((m - M) * 1.4426950408889634f) / L;
            }
            mbar_wait(bar(C_V + 2 * T + wh));
            if (warp == 7) PROF(7 + T);
            const uint32_t a = sb + (wh ? slot(C_V + 2 * T + 1) : slot(C_V + 2 * T)) + ((warp & 3) * 16 + 2 * t) * 256 + ((g ^ (2 * t)) << 4);
            uint4 va[4], vb[4];
#pragma unroll
            for (int i = 0; i < 4; i++) {
                va[i] = lds128(a + (i >> 1) * 256 + (i & 1) * 128);
                vb[i] = lds128(a + 2048 + (i >> 1) * 256 + (i & 1) * 128);
            }
            gemv_step(acc[0], acc[1], va[0], vb[0], pe[T], dsel_lo, dsel_hi);
            gemv_step(acc[2], acc[3], va[1], vb[1], pe[T], dsel_lo, dsel_hi);
            gemv_step(acc[0], acc[1], va[2], vb[2], po[T], dsel_lo, dsel_hi);
            gemv_step(acc[2], acc[3], va[3], vb[3], po[T], dsel_lo, dsel_hi);
            if (T == 0 && V_REUSED) {
                __syncwarp();
                if (lane == 0) mbar_arrive(bar(B_VFREE + wh));
            }
        }
        {
            float r[8];
#pragma unroll
            for (int i = 0; i < 8; i++) {
                const float lo = acc[i >> 2][i & 3], hi = acc[2 + (i >> 2)][i & 3];
                const float send = (t & 1) ? lo : hi, keep = (t & 1) ? hi : lo;
                r[i] = keep + __shfl_xor_sync(0xffffffffu, send, 9);
            }
            float q4[4];
#pragma unroll
            for (int i = 0; i < 4; i++) {
                const float send = (t & 2) ? r[i] : r[4 + i], keep = (t & 2) ? r[4 + i] : r[i];
                q4[i] = (keep + __shfl_xor_sync(0xffffffffu, send, 18)) * fscale;
            }
            const int dim = (t & 1) * 64 + (g ^ (2 * t)) * 8 + (t >> 1) * 4;
            const uint32_t a = sb + OFF_OPART + (s * 8 + warp) * 512 + dim * 4;
            st_async_v4(mapa(a, 0), q4[0], q4[1], q4[2], q4[3], mapa(bar(B_O), 0));
            st_async_v4(mapa(a, 1), q4[0], q4[1], q4[2], q4[3], mapa(bar(B_O), 1));
        }
        if (warp >= 4) return;
        mbar_wait(bar(B_O));
        if (warp == 0) PROF(11);
        {
            float v[16];
#pragma unroll
            for (int i = 0; i < 16; i++) v[i] = lds32f(sb + OFF_OPART + i * 512 + threadIdx.x * 4);
#pragma unroll
            for (int i = 0; i < 8; i++) v[i] += v[i + 8];
#pragma unroll
            for (int i = 0; i < 4; i++) v[i] += v[i + 4];
            v[0] = (v[0] + v[2]) + (v[1] + v[3]);
            const unsigned short ob = __bfloat16_as_ushort(__float2bfloat16_rn(v[0]));
            const int pos = warp * 32 + ((lane >> 1) & 3) * 8 + (lane >> 3) * 2 + (lane & 1);
            asm volatile("st.shared.u16 [%0], %1;" :: "r"(sb + OFF_O + pos * 2), "h"(ob) : "memory");
        }
        asm volatile("bar.arrive 2, 256;" ::: "memory");
    } else if (warp == 8) {
        const size_t kvoff = ((size_t)(b * NHEAD + h) * SK + (SK - WIN) + s * (WIN / 2)) * DH;
        const char* kp = (const char*)(kc + kvoff);
        const char* vp = (const char*)(vc + kvoff);
        uint64_t pol;
        asm volatile("createpolicy.fractional.L2::evict_first.b64 %0, 1.0;" : "=l"(pol));
        asm volatile("barrier.cluster.arrive.relaxed.aligned;" ::: "memory");
        const bool ffn = cl < NUNIT;
        const uint32_t t0 = now_ns();
        const uint2 ed = SchedSel<OOO ? 0 : N0>::get(lane, ffn);
        const uint32_t e = ed.x;
        const int c = e & 255;
        const uint32_t dst = sb + (e >> 24) * CH, mb = bar(c);
        const uint32_t b_land = bar((int)((e >> 8) & 255) - 1), b_free = bar((int)((e >> 16) & 255) - 1);
        const char* src = c < C_V ? kp + (c - C_K) * CH : vp + (c - C_V) * CH;
        const CUtensorMap* map = c < C_K ? &map_wq : c < C_GU ? &map_wo : c == C_WD ? &map_wd : s ? &map_wu : &map_wg;
        const bool linear = c >= C_K && c < C_WO, four = c == C_WD || (c >= C_WO && c < C_GU);
        const int c0 = c < C_K ? h * 2 + s : four ? s * 4 : cl;
        const int c1 = c < C_K ? (c ^ (b * QSWAP)) * 128 : c < C_GU ? h * DH + ((c - C_WO) ^ (b * WSWAP)) * 32
                     : c == C_WD ? cl * 32 : (c - C_GU) * 256;
        named_bar(0, NTHREADS);
        const int nstep = ffn ? C_COUNT : C_GU;
        {
            const int wt = ed.y & 15, whi = (int)((ed.y >> 4) & 255) - wt;
            bool pend = lane < N0 ? wt != 0 : (e & 0xFF0000u) != 0;
            uint32_t tb = lane < N0 ? mb : b_free;
            int next = N0, it = 0;
            while (next < nstep && ++it < SPIN_LIMIT) {
                if (pend && lane <= next) pend = !mbar_test(tb);
                const int infl = __reduce_add_sync(0xffffffffu, pend && lane < next ? wt : 0);
                bool go = lane == next && !pend && infl <= whi;
                if (go && infl > WIN_LO - wt && now_ns() - t0 < (ed.y >> 12)) go = false;
                if (go) {
                    mbar_expect(mb, CH);
                    if (linear) bulk_g2s_stream(dst, src, CH, mb, pol);
                    else tma3d(dst, map, c1, c0, mb);
                    pend = wt != 0; tb = mb;
                }
                next += __any_sync(0xffffffffu, go);
            }
        }
        PROF(18);
    } else if (warp == 13) {
        if (lane == 0) {
#pragma unroll
            for (int i = N0; i < B_COUNT; i++) mbar_init(bar(i), i >= B_WDFREE ? 4 : 1);
            asm volatile("fence.mbarrier_init.release.cluster;" ::: "memory");
            asm volatile("fence.proxy.async.shared::cta;" ::: "memory");
            mbar_expect(bar(B_Q), 256); mbar_expect(bar(B_STAT), 128); mbar_expect(bar(B_O), 8192); mbar_expect(bar(B_F), 512);
        }
        __syncwarp();
        asm volatile("barrier.cluster.arrive.relaxed.aligned;" ::: "memory");
        asm volatile("barrier.cluster.wait.aligned;" ::: "memory");
        named_bar(0, NTHREADS);
        uint4* pf = g_partF + cta * (NUNIT * 2) + lane;
        uint4* pa = g_partA + cta * (NHEAD * 2) + lane;
        const bool has3 = lane < NUNIT * 2 - 64;
        st_post(pa, 0u, 0u, 0u, 0u); st_post(pa + 32, 0u, 0u, 0u, 0u);
        st_post(pf, 0u, 0u, 0u, 0u); st_post(pf + 32, 0u, 0u, 0u, 0u);
        if (has3) st_post(pf + 64, 0u, 0u, 0u, 0u);
        if (lane == 0) {
            asm volatile("prefetch.tensormap [%0];" :: "l"(s ? &map_wu : &map_wg) : "memory");
            asm volatile("prefetch.tensormap [%0];" :: "l"(&map_wd) : "memory");
            asm volatile("prefetch.tensormap [%0];" :: "l"(&map_wo) : "memory");
        }
        const int rb = cta >> 6;
        const uint4 x0 = ldg128(x + rb * D_MODEL + lane * 16), x1 = ldg128(x + rb * D_MODEL + lane * 16 + 8);
        const uint4 g0 = ldg128(gate_w + lane * 16), g1 = ldg128(gate_w + lane * 16 + 8);
        float gate;
        {
            const uint32_t xv[8] = {x0.x, x0.y, x0.z, x0.w, x1.x, x1.y, x1.z, x1.w};
            const uint32_t gv[8] = {g0.x, g0.y, g0.z, g0.w, g1.x, g1.y, g1.z, g1.w};
            float z = 0.f;
#pragma unroll
            for (int i = 0; i < 8; i++) z += rbf(bf_lo(xv[i]) * bf_lo(gv[i])) + rbf(bf_hi(xv[i]) * bf_hi(gv[i]));
#pragma unroll
            for (int o = 16; o > 0; o >>= 1) z += __shfl_xor_sync(0xffffffffu, z, o);
            z = rbf(z);
            gate = rbf(1.f / (1.f + __expf(-z)));
        }
        __syncwarp();
        if (lane == 0) {
            uint32_t v, target; int it = 0;
            asm volatile("atom.add.release.gpu.global.u32 %0, [%1], 1;" : "=r"(v) : "l"(&g_cleared) : "memory");
            target = (v | (NCTA - 1)) + 1;
            PROF(26);
            do {
                asm volatile("ld.acquire.gpu.global.u32 %0, [%1];" : "=r"(v) : "l"(&g_cleared) : "memory");
            } while ((int)(v - target) < 0 && ++it < SPIN_LIMIT);
            mbar_arrive(bar(B_INIT));
            PROF(27);
        }
        __syncwarp();
        auto reduce = [&](float (&r)[4]) {
#pragma unroll
            for (int i = 0; i < 2; i++)
                r[i] = ((lane & 2) ? r[2 + i] : r[i]) + __shfl_xor_sync(0xffffffffu, (lane & 2) ? r[i] : r[2 + i], 2);
            r[0] = ((lane & 4) ? r[1] : r[0]) + __shfl_xor_sync(0xffffffffu, (lane & 4) ? r[0] : r[1], 4);
            r[0] += __shfl_xor_sync(0xffffffffu, r[0], 8);
            r[0] += __shfl_xor_sync(0xffffffffu, r[0], 16);
            return rbf(r[0]);
        };
        float fmix;
        {
            const uint32_t e3 = has3 ? 0u : 0x80000000u;
            uint4 f0 = make_uint4(0u, 0u, 0u, 0u), f1 = f0, f2 = make_uint4(e3, e3, e3, e3);
            mbar_wait(bar(C_V + FPOLL_AT));
            int it = 0;
            do {
                ld_poll_if(f0, pf, full4(f0)); ld_poll_if(f1, pf + 32, full4(f1)); ld_poll_if(f2, pf + 64, full4(f2));
            } while (!__all_sync(0xffffffffu, full4(f0) && full4(f1) && full4(f2)) && ++it < SPIN_LIMIT);
            float r[4];
            r[0] = __uint_as_float(f0.x) + __uint_as_float(f1.x) + __uint_as_float(f2.x);
            r[1] = __uint_as_float(f0.y) + __uint_as_float(f1.y) + __uint_as_float(f2.y);
            r[2] = __uint_as_float(f0.z) + __uint_as_float(f1.z) + __uint_as_float(f2.z);
            r[3] = __uint_as_float(f0.w) + __uint_as_float(f1.w) + __uint_as_float(f2.w);
            fmix = rbf(rbf(1.f - gate) * reduce(r));
        }
        PROF(19);
        mbar_wait(bar(C_WO + 3));
        uint4 p0[NPOLL], p1[NPOLL];
#pragma unroll
        for (int d = 0; d < NPOLL; d++) {
            p0[d] = make_uint4(0u, 0u, 0u, 0u); p1[d] = p0[d];
            ld_poll_if(p0[d], pa, false); ld_poll_if(p1[d], pa + 32, false);
            if (d + 1 < NPOLL) { const uint32_t c = clock(); while ((uint32_t)clock() - c < POLL_GAP) {} }
        }
        float r[4];
        bool done = false;
        for (int it = 0; it < SPIN_LIMIT && !done; it++) {
#pragma unroll
            for (int d = 0; d < NPOLL; d++) {
                const bool k0 = full4(p0[d]), k1 = full4(p1[d]);
                if (__all_sync(0xffffffffu, k0 && k1)) {
                    r[0] = __uint_as_float(p0[d].x) + __uint_as_float(p1[d].x);
                    r[1] = __uint_as_float(p0[d].y) + __uint_as_float(p1[d].y);
                    r[2] = __uint_as_float(p0[d].z) + __uint_as_float(p1[d].z);
                    r[3] = __uint_as_float(p0[d].w) + __uint_as_float(p1[d].w);
                    done = true;
                    break;
                }
                ld_poll_if(p0[d], pa, k0); ld_poll_if(p1[d], pa + 32, k1);
            }
        }
        PROF(20);
        const float res = rbf(gate * reduce(r)) + fmix;
        if (lane < 8) out[cta * 8 + (lane & 1) * 4 + (lane & 2) + (lane >> 2)] = __float2bfloat16_rn(res);
        PROF(21);
    } else {
        asm volatile("barrier.cluster.arrive.relaxed.aligned;" ::: "memory");
        const int fw = warp - 9;
        const int row0 = fw * 128 + (g >> 2) * 64 + (t >> 1) * 4;
        uint2 xw[8];
#pragma unroll
        for (int i = 0; i < 8; i++) xw[i] = __ldg((const uint2*)(x + ((g >> 1) & 1) * D_MODEL + row0 + i * 8));
        named_bar(0, NTHREADS);
        if (cl < NUNIT) {
        mbar_wait(bar(C_GU + (fw >> 1)));
        {
            const uint32_t a0 = sb + ((fw >> 1) ? slot(C_GU + 1) : slot(C_GU)) + ((row0 & 255) + (t & 1)) * 64 + (((g & 3) ^ (t & 2)) << 4);
            const uint32_t a1 = (a0 + 128) ^ 16;
            uint4 wa[8], wb[8];
#pragma unroll
            for (int i = 0; i < 8; i++) { wa[i] = lds128(a0 + i * 512); wb[i] = lds128(a1 + i * 512); }
            const uint32_t sel = (t & 1) ? 0x7632u : 0x5410u;
            float c0[4] = {0.f, 0.f, 0.f, 0.f}, c1[4] = {0.f, 0.f, 0.f, 0.f};
#pragma unroll
            for (int i = 0; i < 8; i++) gemv_step(c0, c1, wa[i], wb[i], __byte_perm(xw[i].x, xw[i].y, sel), sel_lo, sel_hi);
            if ((t >> 1) == (g >> 2)) {
                const uint32_t a = sb + OFF_FPART + (fw * 2 + (g >> 2)) * 256 + (t & 1) * 128 + (g & 3) * 32;
                sts128f(a, c0[0], c0[1], c0[2], c0[3]);
                sts128f(a + 16, c1[0], c1[1], c1[2], c1[3]);
            }
        }
        named_bar(3, 128);
        if (fw == 1 && lane == 0) mbar_arrive(bar(B_GUFREE));
        if (fw == 0) {
            float lo = 0.f, hi = 0.f;
#pragma unroll
            for (int i = 0; i < 8; i++) { float2 v = lds64f(sb + OFF_FPART + i * 256 + lane * 8); lo += v.x; hi += v.y; }
            lo = rbf(lo); hi = rbf(hi);
            const uint32_t a = sb + OFF_GU + s * 256 + lane * 8;
            st_async_v2(mapa(a, 0), lo, hi, mapa(bar(B_F), 0));
            st_async_v2(mapa(a, 1), lo, hi, mapa(bar(B_F), 1));
        }
        mbar_wait(bar(B_F));
        {
            const uint32_t a = sb + OFF_GU + ((g >> 1) & 1) * 128 + t * 8;
            uint32_t hh[4];
#pragma unroll
            for (int i = 0; i < 4; i++) {
                const float2 gv = lds64f(a + i * 32), uv = lds64f(a + 256 + i * 32);
                hh[i] = pack_bf16(gv.x * uv.x, gv.y * uv.y);
            }
            mbar_wait(bar(C_WD));
            const uint32_t a0 = sb + slot(C_WD) + fw * 4096 + 2 * t * 128 + ((g ^ (2 * t)) << 4);
            const uint32_t a1 = (a0 + 128) ^ 16;
            float c0[4] = {0.f, 0.f, 0.f, 0.f}, c1[4] = {0.f, 0.f, 0.f, 0.f};
#pragma unroll
            for (int i = 0; i < 4; i++) {
                const uint4 wa = lds128(a0 + i * 1024), wb = lds128(a1 + i * 1024);
                gemv_step(c0, c1, wa, wb, hh[i], sel_lo, sel_hi);
            }
            if (WD_REUSED) {
                __syncwarp();
                if (lane == 0) mbar_arrive(bar(B_WDFREE));
            }
            float r[4];
#pragma unroll
            for (int i = 0; i < 4; i++) r[i] = (t >> 1) ? c1[i] : c0[i];
            const int cg = s * 32 + fw * 8 + g;
            mbar_wait(bar(B_INIT));
            st_post(&g_partF[(((t & 1) * 64 + cg) * NUNIT + cl) * 2 + (t >> 1)], nz(r[0]), nz(r[1]), nz(r[2]), nz(r[3]));
        }
        if (fw == 0) PROF(22);
        } else mbar_wait(bar(B_INIT));
        {
            const uint32_t a0 = sb + fw * 4096 + 2 * t * 128 + ((g ^ (2 * t)) << 4);
            const uint32_t a1 = (a0 + 128) ^ 16;
            uint4* dst = &g_partA[((b * 64 + s * 32 + fw * 8 + g) * NHEAD + h) * 2 + t];
            uint4 ww[4][8];
            auto fetch = [&](int T) {
                mbar_wait(bar(C_WO + T));
                if (fw == 0) PROF(13 + T);
#pragma unroll
                for (int i = 0; i < 4; i++) {
                    ww[T][2 * i] = lds128(a0 + slot(C_WO + T) + i * 1024);
                    ww[T][2 * i + 1] = lds128(a1 + slot(C_WO + T) + i * 1024);
                }
            };
#pragma unroll
            for (int T = 0; T < NPRE; T++) fetch(T);
            named_bar(2, 256);
            if (fw == 0) PROF(12);
            float c0[4] = {0.f, 0.f, 0.f, 0.f}, c1[4] = {0.f, 0.f, 0.f, 0.f};
            float c2[4] = {0.f, 0.f, 0.f, 0.f}, c3[4] = {0.f, 0.f, 0.f, 0.f};
            uint4 of[4];
#pragma unroll
            for (int T = 0; T < 4; T++) of[T] = lds128(sb + OFF_O + T * 64 + t * 16);
#pragma unroll
            for (int T = 0; T < 4; T++) {
                if (T >= NPRE) fetch(T);
                gemv_step(c0, c1, ww[T][0], ww[T][1], of[T].x, sel_lo, sel_hi);
                gemv_step(c2, c3, ww[T][2], ww[T][3], of[T].y, sel_lo, sel_hi);
                gemv_step(c0, c1, ww[T][4], ww[T][5], of[T].z, sel_lo, sel_hi);
                gemv_step(c2, c3, ww[T][6], ww[T][7], of[T].w, sel_lo, sel_hi);
            }
            if (t < 2) {
                float r[4];
#pragma unroll
                for (int i = 0; i < 4; i++) r[i] = t ? c1[i] + c3[i] : c0[i] + c2[i];
                st_post(dst, nz(r[0]), nz(r[1]), nz(r[2]), nz(r[3]));
            }
            if (fw == 0) PROF(17);
        }
    }
}

}

typedef CUresult (*EncodeFn)(CUtensorMap*, CUtensorMapDataType, cuuint32_t, void*, const cuuint64_t*, const cuuint64_t*,
                             const cuuint32_t*, const cuuint32_t*, CUtensorMapInterleave, CUtensorMapSwizzle,
                             CUtensorMapL2promotion, CUtensorMapFloatOOBfill);

static void make_map(EncodeFn enc, CUtensorMap* m, void* base, uint64_t cols, uint64_t rows,
                     uint32_t box_cols, uint32_t box_rows, uint32_t box_blks) {
    const cuuint64_t dims[3] = {box_cols, rows, cols / box_cols};
    const cuuint64_t strides[2] = {cols * 2, (uint64_t)box_cols * 2};
    const cuuint32_t box[3] = {box_cols, box_rows, box_blks};
    const cuuint32_t es[3] = {1, 1, 1};
    CUresult r = enc(m, CU_TENSOR_MAP_DATA_TYPE_BFLOAT16, 3, base, dims, strides, box, es, CU_TENSOR_MAP_INTERLEAVE_NONE,
        box_cols == 64 ? CU_TENSOR_MAP_SWIZZLE_128B : CU_TENSOR_MAP_SWIZZLE_64B, PROMO, CU_TENSOR_MAP_FLOAT_OOB_FILL_NONE);
    (void)r;
}

extern "C" void kernel_launch(void* const* d_in, const int* in_sizes, int n_in, void* d_out, int out_size) {
    (void)in_sizes; (void)n_in; (void)out_size;
    static EncodeFn enc = nullptr;
    if (!enc) {
        cudaFuncSetAttribute(fused_decode_kernel, cudaFuncAttributeMaxDynamicSharedMemorySize, (int)SMEM_BYTES);
        void* fn = nullptr;
        cudaDriverEntryPointQueryResult qr;
        cudaGetDriverEntryPoint("cuTensorMapEncodeTiled", &fn, cudaEnableDefault, &qr);
        enc = (EncodeFn)fn;
    }
    CUtensorMap map_wq, map_wo, map_wg, map_wu, map_wd;
    make_map(enc, &map_wq, d_in[3], NHEAD * DH, D_MODEL, 64, 128, 1);
    make_map(enc, &map_wo, d_in[4], D_MODEL, NHEAD * DH, 64, 32, 4);
    make_map(enc, &map_wg, d_in[6], FF, D_MODEL, 32, 256, 1);
    make_map(enc, &map_wu, d_in[7], FF, D_MODEL, 32, 256, 1);
    make_map(enc, &map_wd, d_in[8], D_MODEL, FF, 64, 32, 4);
    typedef const __nv_bfloat16* P;
    fused_decode_kernel<<<NCTA, NTHREADS, SMEM_BYTES>>>(map_wq, map_wo, map_wg, map_wu, map_wd, (P)d_in[0], (P)d_in[1],
                                                        (P)d_in[2], (P)d_in[9], (__nv_bfloat16*)d_out);
}
```

```cpp
#include <cuda_runtime.h>
#include <cuda.h>
#include <cuda_bf16.h>
#include <stdint.h>
#include <type_traits>

namespace {

constexpr int D_MODEL = 512;
constexpr int NHEAD   = 32;
constexpr int SK      = 4096;
constexpr int DH      = 128;
constexpr int WIN     = 1024;
constexpr int FF      = 1376;
constexpr int NUNIT   = FF / 32;
constexpr int DUNITS  = 22;
constexpr int OUT_CL0 = 48;
constexpr int NCTA    = 128;
constexpr int NTHREADS = 14 * 32;

constexpr uint32_t CH = 16384;
constexpr int NSLOT = 13;
enum { C_WQ = 0, C_K = 4, C_V = 12, C_WO = 20, C_GU = 24, C_WD = 26, C_COUNT = 29 };
__host__ __device__ constexpr int chunk_at(int i) {
    const char* o = "KqKqKqKqKgKKgKVVVVVVVVooooddd";
    int n = 0;
    for (int j = 0; j < i; j++) n += o[j] == o[i];
    return n + (o[i] == 'q' ? C_WQ : o[i] == 'K' ? C_K : o[i] == 'V' ? C_V : o[i] == 'o' ? C_WO : o[i] == 'g' ? C_GU : C_WD);
}
__host__ __device__ constexpr int pos_of(int c) { int i = 0; while (chunk_at(i) != c) i++; return i; }
__host__ __device__ constexpr uint32_t pos_mask(int c0, int c1) { uint32_t m = 0; for (int c = c0; c < c1; c++) m |= 1u << pos_of(c); return m; }
constexpr uint32_t M_Q = pos_mask(C_WQ, C_K), M_K = pos_mask(C_K, C_V), M_V = pos_mask(C_V, C_WO);
constexpr uint32_t M_O = pos_mask(C_WO, C_GU), M_G = pos_mask(C_GU, C_WD), M_D = pos_mask(C_WD, C_COUNT);
template <int C> struct Slot { static constexpr uint32_t v = (pos_of(C) % NSLOT) * CH; };
constexpr uint32_t WQ_SLOTS = Slot<0>::v / CH | Slot<1>::v / CH << 4 | Slot<2>::v / CH << 8 | Slot<3>::v / CH << 12;
constexpr bool V_REUSED = pos_of(C_V) + NSLOT < C_COUNT;
static_assert(((M_O | M_D | pos_mask(C_V + 2, C_WO)) & ((1u << (C_COUNT - NSLOT)) - 1)) == 0 && !(M_G >> NSLOT & 7), "slot reuse");
constexpr int N0 = 5;
__host__ __device__ constexpr uint32_t burst_mask() { uint32_t m = 0; for (int i = 0; i < N0; i++) m |= 1u << chunk_at(i); return m; }
constexpr uint32_t BURST = burst_mask();
static_assert(BURST < (1u << C_V), "initial burst is wq and K");
template <int I> struct ChunkAt { static constexpr int v = chunk_at(I); };
template <int I, int N, class F> __device__ __forceinline__ void static_for(F&& f) {
    if constexpr (I < N) { f(std::integral_constant<int, I>{}); static_for<I + 1, N>(f); }
}
constexpr int WIN_LO = 4, WIN_HI = 12, PACE_T0 = -1400, PACE_D = 650;

constexpr uint32_t OFF_OPART = NSLOT * CH;
constexpr uint32_t OFF_FPART = OFF_OPART + 8192;
constexpr uint32_t OFF_H     = OFF_FPART + 2048;
constexpr uint32_t OFF_FIN   = OFF_H + 3072;
constexpr uint32_t OFF_Q     = OFF_FIN + 2048;
constexpr uint32_t OFF_O     = OFF_Q + 256;
constexpr uint32_t OFF_STAT  = OFF_O + 256;
constexpr uint32_t OFF_BAR   = OFF_STAT + 128;
constexpr uint32_t SMEM_BYTES = OFF_BAR + 512;
enum { B_INIT = C_COUNT, B_H, B_WQFREE, B_Q, B_STAT, B_O, B_F, B_FIN, B_GUFREE, B_KVFREE, B_COUNT = B_KVFREE + 10 };
static_assert(B_Q == 32, "barrier set-up");

constexpr int SPIN_LIMIT = 1 << 20;

struct __align__(128) Scratch {
    uint4 part[NCTA * NHEAD * 2];
    uint4 hid[NUNIT * 8];
    uint32_t cleared;
};
__device__ Scratch g_scratch;

__device__ __forceinline__ void mbar_init(uint32_t a, uint32_t c) {
    asm volatile("mbarrier.init.shared::cta.b64 [%0], %1;" :: "r"(a), "r"(c) : "memory");
}
__device__ __forceinline__ void mbar_expect(uint32_t a, uint32_t bytes) {
    asm volatile("mbarrier.arrive.expect_tx.shared::cta.b64 _, [%0], %1;" :: "r"(a), "r"(bytes) : "memory");
}
__device__ __forceinline__ void mbar_arrive(uint32_t a) {
    asm volatile("mbarrier.arrive.shared::cta.b64 _, [%0];" :: "r"(a) : "memory");
}
__device__ __forceinline__ void mbar_wait(uint32_t a) {
    uint32_t ok; int it = 0;
#pragma unroll 1
    do {
        asm volatile("{.reg .pred p; mbarrier.try_wait.parity.shared::cta.b64 p, [%1], 0; selp.u32 %0, 1, 0, p;}"
                     : "=r"(ok) : "r"(a) : "memory");
        ++it;
    } while (!ok & (it < SPIN_LIMIT));
}
__device__ __forceinline__ uint32_t now_ns() { uint32_t t; asm volatile("mov.u32 %0, %globaltimer_lo;" : "=r"(t)); return t; }
__device__ __forceinline__ bool mbar_test(uint32_t a) {
    uint32_t ok;
    asm volatile("{.reg .pred p; mbarrier.test_wait.parity.shared::cta.b64 p, [%1], 0; selp.u32 %0, 1, 0, p;}"
                 : "=r"(ok) : "r"(a) : "memory");
    return ok != 0;
}
__device__ __forceinline__ void bulk_g2s_stream(uint32_t dst, const void* src, uint32_t bytes, uint32_t mbar, uint64_t pol) {
    asm volatile("cp.async.bulk.shared::cluster.global.mbarrier::complete_tx::bytes.L2::cache_hint [%0], [%1], %2, [%3], %4;"
                 :: "r"(dst), "l"(src), "r"(bytes), "r"(mbar), "l"(pol) : "memory");
}
__device__ __forceinline__ void tma3d(uint32_t dst, const CUtensorMap* map, int c0, int c1, int c2, uint32_t mbar, uint64_t pol) {
    asm volatile("cp.async.bulk.tensor.3d.shared::cluster.global.mbarrier::complete_tx::bytes.L2::cache_hint [%0], [%1, {%2, %3, %4}], [%5], %6;"
                 :: "r"(dst), "l"(map), "r"(c0), "r"(c1), "r"(c2), "r"(mbar), "l"(pol) : "memory");
}
__device__ __forceinline__ void tma3d(uint32_t dst, const CUtensorMap* map, int c0, int c1, int c2, uint32_t mbar) {
    asm volatile("cp.async.bulk.tensor.3d.shared::cluster.global.mbarrier::complete_tx::bytes [%0], [%1, {%2, %3, %4}], [%5];"
                 :: "r"(dst), "l"(map), "r"(c0), "r"(c1), "r"(c2), "r"(mbar) : "memory");
}
__device__ __forceinline__ uint32_t mapa(uint32_t a, uint32_t rank) {
    uint32_t r; asm("mapa.shared::cluster.u32 %0, %1, %2;" : "=r"(r) : "r"(a), "r"(rank)); return r;
}
__device__ __forceinline__ void st_async_b32(uint32_t a, uint32_t v, uint32_t mbar) {
    asm volatile("st.async.shared::cluster.mbarrier::complete_tx::bytes.b32 [%0], %1, [%2];" :: "r"(a), "r"(v), "r"(mbar) : "memory");
}
__device__ __forceinline__ void st_async_v2(uint32_t a, float x, float y, uint32_t mbar) {
    asm volatile("st.async.shared::cluster.mbarrier::complete_tx::bytes.v2.f32 [%0], {%1, %2}, [%3];" :: "r"(a), "f"(x), "f"(y), "r"(mbar) : "memory");
}
__device__ __forceinline__ void st_async_v4(uint32_t a, float x, float y, float z, float w, uint32_t mbar) {
    asm volatile("st.async.shared::cluster.mbarrier::complete_tx::bytes.v4.f32 [%0], {%1, %2, %3, %4}, [%5];"
                 :: "r"(a), "f"(x), "f"(y), "f"(z), "f"(w), "r"(mbar) : "memory");
}
__device__ __forceinline__ uint4 ldg128(const void* p) {
    uint4 v;
    asm volatile("ld.global.nc.L1::no_allocate.v4.u32 {%0,%1,%2,%3}, [%4];" : "=r"(v.x), "=r"(v.y), "=r"(v.z), "=r"(v.w) : "l"(p));
    return v;
}
__device__ __forceinline__ uint4 lds128(uint32_t a) {
    uint4 v;
    asm volatile("ld.shared.v4.u32 {%0,%1,%2,%3}, [%4];" : "=r"(v.x), "=r"(v.y), "=r"(v.z), "=r"(v.w) : "r"(a) : "memory");
    return v;
}
__device__ __forceinline__ float lds32f(uint32_t a) {
    float v; asm volatile("ld.shared.f32 %0, [%1];" : "=f"(v) : "r"(a) : "memory"); return v;
}
__device__ __forceinline__ float2 lds64f(uint32_t a) {
    float2 v; asm volatile("ld.shared.v2.f32 {%0,%1}, [%2];" : "=f"(v.x), "=f"(v.y) : "r"(a) : "memory"); return v;
}
__device__ __forceinline__ void sts128f(uint32_t a, float x, float y, float z, float w) {
    asm volatile("st.shared.v4.f32 [%0], {%1,%2,%3,%4};" :: "r"(a), "f"(x), "f"(y), "f"(z), "f"(w) : "memory");
}
__device__ __forceinline__ void sts128(uint32_t a, const uint4& v) {
    asm volatile("st.shared.v4.u32 [%0], {%1,%2,%3,%4};" :: "r"(a), "r"(v.x), "r"(v.y), "r"(v.z), "r"(v.w) : "memory");
}
__device__ __forceinline__ uint2 lds64(uint32_t a) {
    uint2 v; asm volatile("ld.shared.v2.u32 {%0,%1}, [%2];" : "=r"(v.x), "=r"(v.y) : "r"(a) : "memory"); return v;
}
__device__ __forceinline__ bool full4(const uint4& v) { return v.x != 0u && v.y != 0u && v.z != 0u && v.w != 0u; }
__device__ __forceinline__ void ld_poll_if(uint4& v, const uint4* p, bool full) {
    asm volatile("{.reg .pred q; setp.eq.u32 q, %5, 0; @q ld.relaxed.gpu.global.v4.u32 {%0,%1,%2,%3}, [%4];}"
                 : "+r"(v.x), "+r"(v.y), "+r"(v.z), "+r"(v.w) : "l"(p), "r"((uint32_t)full) : "memory");
}
__device__ __forceinline__ void st_post(uint4* p, uint32_t x, uint32_t y, uint32_t z, uint32_t w) {
    asm volatile("st.relaxed.gpu.global.v4.u32 [%0], {%1,%2,%3,%4};" :: "l"(p), "r"(x), "r"(y), "r"(z), "r"(w) : "memory");
}
__device__ __forceinline__ uint32_t nz(float v) {
    uint32_t r; asm("max.u32 %0, %1, 1;" : "=r"(r) : "r"(__float_as_uint(v))); return r;
}
__device__ __forceinline__ void mma16816(float (&c)[4], uint32_t a0, uint32_t a1, uint32_t a2, uint32_t a3, uint32_t b0, uint32_t b1) {
    asm volatile("mma.sync.aligned.m16n8k16.row.col.f32.bf16.bf16.f32 {%0,%1,%2,%3}, {%4,%5,%6,%7}, {%8,%9}, {%0,%1,%2,%3};"
                 : "+f"(c[0]), "+f"(c[1]), "+f"(c[2]), "+f"(c[3]) : "r"(a0), "r"(a1), "r"(a2), "r"(a3), "r"(b0), "r"(b1));
}
__device__ __forceinline__ uint32_t pack_bf16(float lo, float hi) {
    uint32_t r; asm("cvt.rn.bf16x2.f32 %0, %1, %2;" : "=r"(r) : "f"(hi), "f"(lo)); return r;
}
__device__ __forceinline__ float rbf(float v) { return __uint_as_float(pack_bf16(0.f, v)); }
__device__ __forceinline__ float bf_lo(uint32_t u) { return __uint_as_float(u << 16); }
__device__ __forceinline__ float bf_hi(uint32_t u) { return __uint_as_float(u & 0xFFFF0000u); }
__device__ __forceinline__ void named_bar(int id, int n) { asm volatile("bar.sync %0, %1;" :: "r"(id), "r"(n) : "memory"); }

__device__ __forceinline__ void gemv(float (&c)[4], const uint4& w, uint32_t b0, uint32_t b1) {
    mma16816(c, w.x, w.y, w.z, w.w, b0, b1);
}
__device__ __forceinline__ uint32_t pick(uint32_t v, uint32_t sel) { return __byte_perm(v, 0u, sel); }

__global__ void __cluster_dims__(2, 1, 1) __launch_bounds__(NTHREADS, 1)
fused_decode_kernel(const __nv_bfloat16* __restrict__ kc, const __nv_bfloat16* __restrict__ x,
                    const __nv_bfloat16* __restrict__ gate_w, __nv_bfloat16* __restrict__ out, Scratch* scr,
                    const __grid_constant__ CUtensorMap map_wq, const __grid_constant__ CUtensorMap map_v,
                    const __grid_constant__ CUtensorMap map_wo, const __grid_constant__ CUtensorMap map_wg,
                    const __grid_constant__ CUtensorMap map_wu, const __grid_constant__ CUtensorMap map_wd) {
    extern __shared__ __align__(1024) unsigned char smem_raw[];
    const uint32_t sb = (uint32_t)__cvta_generic_to_shared(smem_raw);
    const int warp = threadIdx.x >> 5, lane = threadIdx.x & 31;
    const int g = lane >> 2, t = lane & 3;
    const int cta = blockIdx.x;
    const int s = cta & 1;
    const int cl = cta >> 1;
    const int b = cl & 1, h = cl >> 1;
    const int oc = cl - OUT_CL0;
    const bool outc = (unsigned)oc < 16u;
    auto bar = [&](int i) { return sb + OFF_BAR + 8u * i; };
    constexpr uint32_t NONE = 0x4444u;
    const uint32_t sel_lo = (g & 1) ? 0x1044u : 0x4410u;
    const uint32_t sel_hi = (g & 1) ? 0x3244u : 0x4432u;

    if (warp == 8) {
        const int key0 = (b * NHEAD + h) * SK + (SK - WIN) + s * (WIN / 2);
        const char* kp = (const char*)(kc + (size_t)key0 * DH);
        uint64_t pol;
        asm volatile("createpolicy.fractional.L2::evict_first.b64 %0, 1.0;" : "=l"(pol));
        if (lane == 0) {
            asm volatile("cp.async.bulk.prefetch.L2.global.L2::cache_hint [%0], %1, %2;" :: "l"(kp), "r"(CH), "l"(pol) : "memory");
            static_for<0, N0>([&](auto I) { mbar_init(bar(ChunkAt<I.value>::v), 1); });
            asm volatile("fence.proxy.async.shared::cta;" ::: "memory");
            static_for<0, N0>([&](auto I) {
                constexpr int i = I.value, c = ChunkAt<i>::v;
                mbar_expect(bar(c), CH);
                if constexpr (c < C_K) tma3d(sb + i * CH, &map_wq, 0, c * 128, h * 2 + s, bar(c));
                else bulk_g2s_stream(sb + i * CH, kp + (c - C_K) * CH, CH, bar(c), pol);
            });
        }
        __syncwarp();
        asm volatile("barrier.cluster.arrive.relaxed.aligned;" ::: "memory");
        const uint32_t t0 = now_ns();
        const uint32_t bit = 1u << lane, le = bit | (bit - 1);
        const bool isq = M_Q & bit, isk = M_K & bit, isv = M_V & bit, iso = M_O & bit, isg = M_G & bit, isd = M_D & bit;
        const int idx = __popc((isq ? M_Q : isk ? M_K : isv ? M_V : iso ? M_O : isg ? M_G : M_D) & (bit - 1));
        const int c = idx + (isq ? C_WQ : isk ? C_K : isv ? C_V : iso ? C_WO : isg ? C_GU : C_WD);
        const int pc = __shfl_up_sync(0xffffffffu, c, NSLOT);
        const uint32_t dst = sb + (lane % NSLOT) * CH, mb = bar(c);
        const CUtensorMap* map = isq ? &map_wq : isv ? &map_v : iso ? &map_wo : isd ? &map_wd : idx ? &map_wu : &map_wg;
        const int c0 = isd ? oc * 32 : 0;
        const int c1 = isq ? idx * 128 : isv ? key0 * 2 + idx * 128 : iso ? h * DH + idx * 32 : isg ? s * 256 : 0;
        const int c2 = isq ? h * 2 + s : iso ? s * 4 : isg ? cl : isd ? DUNITS + (s ? idx : -1 - idx) * 8 : 0;
        const bool skip = isg ? cl >= NUNIT : isd && !outc;
        const int wt = isq ? 1 : iso ? 1 : isg ? 0 : isd ? 1 : 2;
        const int due = PACE_T0 + __popc((M_K | M_V) & le) * PACE_D + __popc(M_Q & le) * (PACE_D / 2) + __popc(M_O & le) * (PACE_D / 2)
                      + __popc(M_G & le) * (PACE_D * 43 / 64) + __popc(M_D & le) * (PACE_D * 43 / 192);
        bool pend = lane < N0 ? wt != 0 : lane >= NSLOT && !skip;
        uint32_t tb = lane < N0 ? mb : bar(pc < C_K ? B_WQFREE : pc >= C_GU ? B_GUFREE : B_KVFREE - C_K + pc);
        named_bar(0, NTHREADS);
        int next = N0, it = 0;
#pragma unroll 1
        while (next < C_COUNT && ++it < SPIN_LIMIT) {
            if (pend && lane <= next) pend = !mbar_test(tb);
            const int infl = __reduce_add_sync(0xffffffffu, pend && lane < next ? wt : 0) + wt;
            const bool go = lane == next && !pend && (skip || infl <= WIN_LO || (infl <= WIN_HI && (int)(now_ns() - t0) >= due));
            if (go && !skip) {
                mbar_expect(mb, CH);
                if (isk) bulk_g2s_stream(dst, kp + idx * CH, CH, mb, pol);
                else if (isv || isg || isd) tma3d(dst, map, c0, c1, c2, mb, pol);
                else tma3d(dst, map, c0, c1, c2, mb);
                pend = wt != 0; tb = mb;
            }
            next += __any_sync(0xffffffffu, go);
        }
    } else if (warp < 8) {
        uint32_t xr[8];
#pragma unroll
        for (int i = 0; i < 8; i++) xr[i] = __ldg((const uint32_t*)(x + b * D_MODEL + warp * 64 + i * 8 + t * 2));
        asm volatile("barrier.cluster.arrive.relaxed.aligned;" ::: "memory");
        named_bar(0, NTHREADS);
        mbar_wait(bar(C_WQ + (warp >> 1)));
        {
            const uint32_t a0 = sb + ((WQ_SLOTS >> (4 * (warp >> 1))) & 15) * CH + ((warp & 1) * 64 + 2 * t) * 128 + ((g ^ (2 * t)) << 4);
            const uint32_t a1 = (a0 + 128) ^ 16;
            const uint32_t sel = (g & 4) ? sel_hi : sel_lo, s0 = (g & 2) ? NONE : sel, s1 = (g & 2) ? sel : NONE;
            float c0[4] = {0.f, 0.f, 0.f, 0.f}, c1[4] = {0.f, 0.f, 0.f, 0.f};
#pragma unroll
            for (int i = 0; i < 8; i++) {
                const uint4 wa = lds128(a0 + i * 1024), wb = lds128(a1 + i * 1024);
                const uint32_t b0 = pick(xr[i], s0), b1 = pick(xr[i], s1);
                gemv(c0, wa, b0, b1); gemv(c1, wb, b0, b1);
            }
            const bool odd = t & 2;
            sts128f(sb + OFF_OPART + warp * 512 + (t >> 1) * 256 + g * 32 + (t & 1) * 16,
                    odd ? c1[0] : c0[0], odd ? c1[1] : c0[1], odd ? c1[2] : c0[2], odd ? c1[3] : c0[3]);
        }
        named_bar(1, 256);
        if (warp == 1 && lane == 0) mbar_arrive(bar(B_WQFREE));
        if (warp == 0) {
            float lo = 0.f, hi = 0.f;
#pragma unroll
            for (int i = 0; i < 16; i++) { float2 v = lds64f(sb + OFF_OPART + i * 256 + lane * 8); lo += v.x; hi += v.y; }
            const uint32_t qq = pack_bf16(lo, hi);
            const uint32_t a = sb + OFF_Q + s * 128 + g * 16 + (t & 1) * 8 + (t >> 1) * 4;
            st_async_b32(mapa(a, 0), qq, mapa(bar(B_Q), 0));
            st_async_b32(mapa(a, 1), qq, mapa(bar(B_Q), 1));
        }
        mbar_wait(bar(B_Q));
        uint2 qf[4];
#pragma unroll
        for (int j = 0; j < 4; j++) qf[j] = lds64(sb + OFF_Q + ((j ^ ((g >> 1) & 1)) << 6) + t * 16 + (g & 1) * 8);

        const int wh = warp >> 2;
        const bool valid = ((t ^ g) & 1) == 0;
        float sc[8];
        static_for<0, 4>([&](auto TT) {
            constexpr int T = TT.value;
            mbar_wait(bar(C_K + 2 * T + wh));
            const uint32_t a = sb + (wh ? Slot<C_K + 2 * T + 1>::v : Slot<C_K + 2 * T>::v) + ((warp & 3) * 16 + g) * 256 + t * 16;
            float c0[4] = {0.f, 0.f, 0.f, 0.f}, c1[4] = {0.f, 0.f, 0.f, 0.f};
#pragma unroll
            for (int j = 0; j < 4; j++) {
                const uint4 ka = lds128(a + ((j ^ (g & 1)) << 6)), kb = lds128(a + 2048 + ((j ^ (g & 1)) << 6));
                gemv(c0, ka, qf[j].x, qf[j].y); gemv(c1, kb, qf[j].x, qf[j].y);
            }
            const uint32_t s2 = pack_bf16(c0[0] + c0[3], c1[0] + c1[3]);
            const uint32_t s3 = pack_bf16(bf_lo(s2) * 0.08838834764831845f, bf_hi(s2) * 0.08838834764831845f);
            sc[2 * T] = bf_lo(s3); sc[2 * T + 1] = bf_hi(s3);
            __syncwarp();
            if (lane == 0) mbar_arrive(bar(B_KVFREE + 2 * T + wh));
        });
        float m = sc[0];
#pragma unroll
        for (int i = 1; i < 8; i++) m = fmaxf(m, sc[i]);
        m = __shfl_sync(0xffffffffu, m, valid ? lane : lane ^ 1);
        m = fmaxf(m, __shfl_xor_sync(0xffffffffu, m, 4));
        m = fmaxf(m, __shfl_xor_sync(0xffffffffu, m, 8));
        m = fmaxf(m, __shfl_xor_sync(0xffffffffu, m, 16));
        uint32_t pa[4], pb[4];
        float l = 0.f;
        const float ms = (m == -INFINITY) ? 0.f : m;
#pragma unroll
        for (int T = 0; T < 4; T++) {
            const float p0 = exp2f((sc[2 * T] - ms) * 1.4426950408889634f);
            const float p1 = exp2f((sc[2 * T + 1] - ms) * 1.4426950408889634f);
            l += p0 + p1;
            const uint32_t pp = pack_bf16(p0, p1);
            pa[T] = __shfl_sync(0xffffffffu, pp, 4 * t + (t & 1));
            pb[T] = __shfl_sync(0xffffffffu, pp, 4 * t + (t & 1) + 16);
        }
        l += __shfl_xor_sync(0xffffffffu, l, 5);
        l += __shfl_xor_sync(0xffffffffu, l, 8);
        l += __shfl_xor_sync(0xffffffffu, l, 16);
        if ((lane & 29) == 0) st_async_v2(mapa(sb + OFF_STAT + (s * 8 + warp) * 8, lane >> 1), m, l, mapa(bar(B_STAT), lane >> 1));

        const uint32_t s0l = (g & 2) ? NONE : sel_lo, s1l = (g & 2) ? sel_lo : NONE;
        const uint32_t s0h = (g & 2) ? NONE : sel_hi, s1h = (g & 2) ? sel_hi : NONE;
        float acc[4][4];
#pragma unroll
        for (int i = 0; i < 4; i++) { acc[i][0] = acc[i][1] = acc[i][2] = acc[i][3] = 0.f; }
        float fscale = 0.f;
        static_for<0, 4>([&](auto TT) {
            constexpr int T = TT.value;
            if (T == 3) {
                mbar_wait(bar(B_STAT));
                const float2 st = lds64f(sb + OFF_STAT + (lane & 15) * 8);
                float M = st.x;
#pragma unroll
                for (int o = 1; o < 16; o <<= 1) M = fmaxf(M, __shfl_xor_sync(0xffffffffu, M, o));
                float L = st.y * exp2f((st.x - M) * 1.4426950408889634f);
#pragma unroll
                for (int o = 1; o < 16; o <<= 1) L += __shfl_xor_sync(0xffffffffu, L, o);
                fscale = exp2f((m - M) * 1.4426950408889634f) / L;
            }
            mbar_wait(bar(C_V + 2 * T + wh));
            const uint32_t a0 = sb + (wh ? Slot<C_V + 2 * T + 1>::v : Slot<C_V + 2 * T>::v) + (warp & 3) * 4096 + t * 256 + ((g ^ (2 * t)) << 4);
            const uint32_t a1 = (a0 + 128) ^ 16;
            uint4 va[4], vb[4];
#pragma unroll
            for (int i = 0; i < 4; i++) { va[i] = lds128(a0 + i * 1024); vb[i] = lds128(a1 + i * 1024); }
#pragma unroll
            for (int i = 0; i < 4; i++) {
                const uint32_t p = (i & 1) ? pb[T] : pa[T];
                const uint32_t b0 = pick(p, (i & 2) ? s0h : s0l), b1 = pick(p, (i & 2) ? s1h : s1l);
                gemv(acc[(i & 1) * 2], va[i], b0, b1); gemv(acc[(i & 1) * 2 + 1], vb[i], b0, b1);
            }
            if (T == 0 && V_REUSED) {
                __syncwarp();
                if (lane == 0) mbar_arrive(bar(B_KVFREE + 8 + wh));
            }
        });
        {
            float r[4];
#pragma unroll
            for (int i = 0; i < 4; i++) r[i] = ((t & 2) ? acc[1][i] + acc[3][i] : acc[0][i] + acc[2][i]) * fscale;
            const uint32_t a = sb + OFF_OPART + (s * 8 + warp) * 512 + (t >> 1) * 256 + g * 32 + (t & 1) * 16;
            st_async_v4(mapa(a, 0), r[0], r[1], r[2], r[3], mapa(bar(B_O), 0));
            st_async_v4(mapa(a, 1), r[0], r[1], r[2], r[3], mapa(bar(B_O), 1));
        }
        if (warp < 4) {
            mbar_wait(bar(B_O));
            float v[16];
#pragma unroll
            for (int i = 0; i < 16; i++) v[i] = lds32f(sb + OFF_OPART + i * 512 + threadIdx.x * 4);
#pragma unroll
            for (int i = 0; i < 8; i++) v[i] += v[i + 8];
#pragma unroll
            for (int i = 0; i < 4; i++) v[i] += v[i + 4];
            v[0] = (v[0] + v[2]) + (v[1] + v[3]);
            const unsigned short ob = (unsigned short)pack_bf16(v[0], 0.f);
            const int pos = warp * 32 + ((lane >> 1) & 3) * 8 + (lane >> 3) * 2 + (lane & 1);
            asm volatile("st.shared.u16 [%0], %1;" :: "r"(sb + OFF_O + pos * 2), "h"(ob) : "memory");
            asm volatile("bar.arrive 2, 256;" ::: "memory");
        }
        if (outc) {
            const uint32_t a = sb + warp * 2048 + ((lane >> 4) * 8 + (lane & 7)) * 64 + ((((lane >> 3) & 1) ^ ((lane >> 1) & 3) ^ (s * 2 + wh)) << 4);
            uint32_t fd = mapa(sb + OFF_FIN + (s * 8 + warp) * 128 + g * 16, t & 1), fb = mapa(bar(B_FIN), t & 1);
            asm volatile("" : "+r"(fd), "+r"(fb));
            uint4 hf[3];
            mbar_wait(bar(B_H));
#pragma unroll
            for (int i = 0; i < 3; i++) hf[i] = lds128(sb + OFF_H + (warp + 8 * (s ? i : 2 - i)) * 128 + (g & 2) * 32 + t * 16);
            float c[4][4];
#pragma unroll
            for (int i = 0; i < 4; i++) { c[i][0] = c[i][1] = c[i][2] = c[i][3] = 0.f; }
            static_for<0, 3>([&](auto II) {
                constexpr int i = II.value;
                if (i == 2 && (unsigned)(DUNITS + (s ? 16 : -24) + warp) >= (unsigned)NUNIT) return;
                mbar_wait(bar(C_WD + i));
                uint4 w[4];
#pragma unroll
                for (int j = 0; j < 4; j++)
                    asm volatile("ldmatrix.sync.aligned.m8n8.x4.trans.shared.b16 {%0,%1,%2,%3}, [%4];"
                                 : "=r"(w[j].x), "=r"(w[j].y), "=r"(w[j].z), "=r"(w[j].w)
                                 : "r"((a ^ ((j & 1) * 32)) + Slot<C_WD + i>::v + (j >> 1) * 1024) : "memory");
                gemv(c[0], w[0], hf[i].x, hf[i].y); gemv(c[1], w[1], hf[i].x, hf[i].y);
                gemv(c[2], w[2], hf[i].z, hf[i].w); gemv(c[3], w[3], hf[i].z, hf[i].w);
            });
            asm volatile("{.reg .pred q; setp.lt.u32 q, %6, 2;"
                         " @q st.async.weak.shared::cluster.mbarrier::complete_tx::bytes.v4.f32 [%0], {%1,%2,%3,%4}, [%5];}"
                         :: "r"(fd), "f"(c[0][0] + c[2][0]), "f"(c[0][2] + c[2][2]), "f"(c[1][0] + c[3][0]), "f"(c[1][2] + c[3][2]),
                            "r"(fb), "r"(t) : "memory");
        }
    } else if (warp == 13) {
        if (lane >= C_V || !((BURST >> lane) & 1)) mbar_init(bar(lane), 1);
        if (lane < B_COUNT - 32) mbar_init(bar(32 + lane), 32 + lane >= B_GUFREE ? 4 : 1);
        asm volatile("fence.mbarrier_init.release.cluster;" ::: "memory");
        asm volatile("fence.proxy.async.shared::cta;" ::: "memory");
        if (lane < 5) mbar_expect(bar(B_Q + lane), 128u << ((0x44601u >> (4 * lane)) & 15));
        __syncwarp();
        asm volatile("barrier.cluster.arrive.relaxed.aligned;" ::: "memory");
        asm volatile("barrier.cluster.wait.aligned;" ::: "memory");
        named_bar(0, NTHREADS);
        mbar_wait(bar(C_K));
        if (lane == 0) {
            asm volatile("prefetch.tensormap [%0];" :: "l"(&map_wg) : "memory");
            asm volatile("prefetch.tensormap [%0];" :: "l"(&map_wu) : "memory");
            asm volatile("prefetch.tensormap [%0];" :: "l"(&map_v) : "memory");
            asm volatile("prefetch.tensormap [%0];" :: "l"(&map_wo) : "memory");
            asm volatile("prefetch.tensormap [%0];" :: "l"(&map_wd) : "memory");
        }
        mbar_wait(bar(C_WQ + 2));
        uint4* pa = scr->part + cta * (NHEAD * 2) + lane;
        st_post(pa, 0u, 0u, 0u, 0u); st_post(pa + 32, 0u, 0u, 0u, 0u);
        if (cl < NUNIT && lane < 4) st_post(scr->hid + cta * 4 + lane, 0u, 0u, 0u, 0u);
        __syncwarp();
        if (lane == 0) {
            uint32_t v, target; int it = 0;
            asm volatile("atom.add.release.gpu.global.u32 %0, [%1], 1;" : "=r"(v) : "l"(&scr->cleared) : "memory");
            target = (v | (NCTA - 1)) + 1;
#pragma unroll 1
            do {
                asm volatile("ld.acquire.gpu.global.u32 %0, [%1];" : "=r"(v) : "l"(&scr->cleared) : "memory");
            } while ((int)(v - target) < 0 && ++it < SPIN_LIMIT);
            mbar_arrive(bar(B_INIT));
        }
        __syncwarp();
        if (!outc) return;
        mbar_wait(bar(C_V + 3));
#pragma unroll 1
        for (int j = 0; j < 2; j++) {
            const int q = (DUNITS - 24 + s * 24) * 8 + j * 96 + lane;
            const uint4* ph = scr->hid + q;
            const bool pad0 = q < 0, pad1 = q + 32 >= NUNIT * 8, pad2 = q + 64 >= NUNIT * 8;
            uint4 f0 = make_uint4(0u, 0u, 0u, 0u), f1 = f0, f2 = f0;
            int it = 0;
#pragma unroll 1
            do {
                ld_poll_if(f0, ph, pad0); ld_poll_if(f1, ph + 32, pad1); ld_poll_if(f2, ph + 64, pad2);
            } while (!__all_sync(0xffffffffu, (pad0 || full4(f0)) && (pad1 || full4(f1)) && (pad2 || full4(f2))) && ++it < SPIN_LIMIT);
            const uint32_t a = sb + OFF_H + j * 1536 + lane * 16;
            sts128(a, f0); sts128(a + 512, f1); sts128(a + 1024, f2);
        }
        __syncwarp();
        if (lane == 0) mbar_arrive(bar(B_H));
    } else {
        if (threadIdx.x == 9 * 32) asm volatile("prefetch.tensormap [%0];" :: "l"(&map_wq) : "memory");
        __syncwarp();
        asm volatile("barrier.cluster.arrive.relaxed.aligned;" ::: "memory");
        const int fw = warp - 9;
        uint2 xw[8];
#pragma unroll
        for (int i = 0; i < 8; i++) xw[i] = __ldg((const uint2*)(x + (g >> 2) * D_MODEL + s * 256 + fw * 64 + (t >> 1) * 4 + i * 8));
        named_bar(0, NTHREADS);
        if (cl < NUNIT) {
            const uint32_t a0 = sb + ((g & 4) ? Slot<C_GU + 1>::v : Slot<C_GU>::v)
                              + (fw * 64 + (t >> 1) * 4 + (t & 1)) * 64 + (((g & 3) ^ (t & 2)) << 4);
            const uint32_t a1 = (a0 + 128) ^ 16;
            const uint32_t sel = (t & 1) ? sel_hi : sel_lo, s0 = (g & 2) ? NONE : sel, s1 = (g & 2) ? sel : NONE;
            float c0[4] = {0.f, 0.f, 0.f, 0.f}, c1[4] = {0.f, 0.f, 0.f, 0.f};
            mbar_wait(bar(C_GU));
            mbar_wait(bar(C_GU + 1));
#pragma unroll
            for (int i = 0; i < 8; i++) {
                const uint4 wa = lds128(a0 + i * 512), wb = lds128(a1 + i * 512);
                gemv(c0, wa, pick(xw[i].x, s0), pick(xw[i].x, s1));
                gemv(c1, wb, pick(xw[i].y, s0), pick(xw[i].y, s1));
            }
            st_async_v4(mapa(sb + OFF_FPART + (s * 4 + fw) * 256 + g * 32 + (t & 1) * 16, t >> 1),
                        c0[0] + c1[0], c0[1] + c1[1], c0[2] + c1[2], c0[3] + c1[3], mapa(bar(B_F), t >> 1));
        }
        __syncwarp();
        if (lane == 0) mbar_arrive(bar(B_GUFREE));
        mbar_wait(bar(B_INIT));
        if (fw == 0 && cl < NUNIT) {
            mbar_wait(bar(B_F));
            float lo = 0.f, hi = 0.f;
#pragma unroll
            for (int i = 0; i < 8; i++) { float2 v = lds64f(sb + OFF_FPART + i * 256 + lane * 8); lo += v.x; hi += v.y; }
            const uint32_t mine = pack_bf16(lo, hi), other = __shfl_xor_sync(0xffffffffu, mine, 16);
            uint32_t hh = pack_bf16(bf_lo(mine) * bf_lo(other), bf_hi(mine) * bf_hi(other));
            if (hh == 0u) hh = 0x80008000u;
            if (lane < 16)
                asm volatile("st.relaxed.gpu.global.u32 [%0], %1;"
                             :: "l"((uint32_t*)(scr->hid + cta * 4) + t * 4 + g), "r"(hh) : "memory");
        }
        float gate = 0.f;
        if (outc) {
#pragma unroll 1
        for (int j = 0; j < 2; j++) {
            const uint4 xv = ldg128(x + s * D_MODEL + j * 256 + lane * 8), gv = ldg128(gate_w + j * 256 + lane * 8);
            const uint32_t xx[4] = {xv.x, xv.y, xv.z, xv.w}, gg[4] = {gv.x, gv.y, gv.z, gv.w};
#pragma unroll
            for (int i = 0; i < 4; i++) {
                const uint32_t p = pack_bf16(bf_lo(xx[i]) * bf_lo(gg[i]), bf_hi(xx[i]) * bf_hi(gg[i]));
                gate += bf_lo(p) + bf_hi(p);
            }
        }
#pragma unroll
        for (int o = 16; o > 0; o >>= 1) gate += __shfl_xor_sync(0xffffffffu, gate, o);
        gate = rbf(1.f / (1.f + __expf(-rbf(gate))));
        }
        {
            const uint32_t a0 = sb + fw * 4096 + 2 * t * 128 + ((g ^ (2 * t)) << 4);
            const uint32_t a1 = (a0 + 128) ^ 16;
            const uint32_t s0l = (g & 2) ? NONE : sel_lo, s1l = (g & 2) ? sel_lo : NONE;
            const uint32_t s0h = (g & 2) ? NONE : sel_hi, s1h = (g & 2) ? sel_hi : NONE;
            uint4* dst = &scr->part[(((s * 32 + fw * 8 + g) * 2 + b) * NHEAD + h) * 2 + t];
            uint4 ww[4][8];
            auto fetch = [&](auto TT) {
                constexpr int T = TT.value;
                mbar_wait(bar(C_WO + T));
#pragma unroll
                for (int i = 0; i < 4; i++) {
                    ww[T][2 * i] = lds128(a0 + Slot<C_WO + T>::v + i * 1024);
                    ww[T][2 * i + 1] = lds128(a1 + Slot<C_WO + T>::v + i * 1024);
                }
            };
            static_for<0, 1>(fetch);
            named_bar(2, 256);
            float c[4][4];
#pragma unroll
            for (int i = 0; i < 4; i++) { c[i][0] = c[i][1] = c[i][2] = c[i][3] = 0.f; }
            uint4 of[4];
#pragma unroll
            for (int T = 0; T < 4; T++) of[T] = lds128(sb + OFF_O + T * 64 + t * 16);
            static_for<0, 4>([&](auto TT) {
                constexpr int T = TT.value;
                if constexpr (T >= 1) fetch(TT);
                const uint32_t o4[4] = {of[T].x, of[T].y, of[T].z, of[T].w};
#pragma unroll
                for (int i = 0; i < 4; i++) {
                    gemv(c[(2 * i) & 3], ww[T][2 * i], pick(o4[i], s0l), pick(o4[i], s1l));
                    gemv(c[(2 * i + 1) & 3], ww[T][2 * i + 1], pick(o4[i], s0h), pick(o4[i], s1h));
                }
            });
            uint32_t r[4];
#pragma unroll
            for (int i = 0; i < 4; i++) r[i] = nz((c[0][i] + c[1][i]) + (c[2][i] + c[3][i]));
            asm volatile("{.reg .pred q; setp.lt.u32 q, %5, 2; @q st.relaxed.gpu.global.v4.u32 [%0], {%1,%2,%3,%4};}"
                         :: "l"(dst), "r"(r[0]), "r"(r[1]), "r"(r[2]), "r"(r[3]), "r"(t) : "memory");
        }
        if (!outc) return;
        const uint32_t* pa = (const uint32_t*)(scr->part + ((oc * 4 + fw) * 2 + s) * (NHEAD * 2)) + lane;
        const uint32_t af = sb + OFF_FIN + (lane >> 3) * 512 + (lane & 7) * 16 + (fw ^ (lane >> 3)) * 4;
        uint32_t gates = pack_bf16(gate, 1.f - gate);
        __nv_bfloat16* po = out + s * D_MODEL + oc * 32 + fw * 8 + (lane & 7);
        asm volatile("" : "+r"(gates), "+l"(po));
        { const uint32_t c = clock(); while ((uint32_t)clock() - c < 300u) {} }
        uint32_t p[8] = {0u, 0u, 0u, 0u, 0u, 0u, 0u, 0u};
        int it = 0;
        bool done = false;
        auto sum4 = [](float v) {
            return (v + __shfl_xor_sync(0xffffffffu, v, 8)) + (__shfl_xor_sync(0xffffffffu, v, 16) + __shfl_xor_sync(0xffffffffu, v, 24));
        };
        float ra, rf = 0.f;
#pragma unroll 1
        do {
#pragma unroll
            for (int i = 0; i < 8; i++)
                asm volatile("{.reg .pred q; setp.eq.u32 q, %0, 0; @q ld.relaxed.gpu.global.u32 %0, [%1];}" : "+r"(p[i]) : "l"(pa + i * 32) : "memory");
            done = mbar_test(bar(B_FIN));
            rf = sum4((lds32f(af) + lds32f(af + 128)) + (lds32f(af + 256) + lds32f(af + 384)));
            const uint32_t mn = min(min(min(p[0], p[1]), min(p[2], p[3])), min(min(p[4], p[5]), min(p[6], p[7])));
            const bool full = mn != 0u;
            ra = sum4(((__uint_as_float(p[0]) + __uint_as_float(p[1])) + (__uint_as_float(p[2]) + __uint_as_float(p[3])))
                    + ((__uint_as_float(p[4]) + __uint_as_float(p[5])) + (__uint_as_float(p[6]) + __uint_as_float(p[7]))));
            if (__all_sync(0xffffffffu, full)) break;
        } while (++it < SPIN_LIMIT);
        if (!__all_sync(0xffffffffu, done)) {
            mbar_wait(bar(B_FIN));
            __syncwarp();
            rf = sum4((lds32f(af) + lds32f(af + 128)) + (lds32f(af + 256) + lds32f(af + 384)));
        }
        const uint32_t both = pack_bf16(ra, rf);
        const __nv_bfloat162 mixed = __hmul2_rn(*(const __nv_bfloat162*)&both, *(const __nv_bfloat162*)&gates);
        asm volatile("st.global.u16 [%0], %1;" :: "l"(po), "h"(__bfloat16_as_ushort(__hadd_rn(mixed.x, mixed.y))) : "memory");
    }
}

}

typedef CUresult (*EncodeFn)(CUtensorMap*, CUtensorMapDataType, cuuint32_t, void*, const cuuint64_t*, const cuuint64_t*,
                             const cuuint32_t*, const cuuint32_t*, CUtensorMapInterleave, CUtensorMapSwizzle,
                             CUtensorMapL2promotion, CUtensorMapFloatOOBfill);

static void make_map(EncodeFn enc, CUtensorMap* m, void* base, uint64_t d0, uint64_t d1, uint64_t d2, uint64_t s1, uint64_t s2,
                     uint32_t b0, uint32_t b1, uint32_t b2) {
    const cuuint64_t dims[3] = {d0, d1, d2};
    const cuuint64_t strides[2] = {s1, s2};
    const cuuint32_t box[3] = {b0, b1, b2};
    const cuuint32_t es[3] = {1, 1, 1};
    enc(m, CU_TENSOR_MAP_DATA_TYPE_BFLOAT16, 3, base, dims, strides, box, es, CU_TENSOR_MAP_INTERLEAVE_NONE,
        b0 == 64 ? CU_TENSOR_MAP_SWIZZLE_128B : CU_TENSOR_MAP_SWIZZLE_64B, CU_TENSOR_MAP_L2_PROMOTION_NONE, CU_TENSOR_MAP_FLOAT_OOB_FILL_NONE);
}

extern "C" void kernel_launch(void* const* d_in, const int* in_sizes, int n_in, void* d_out, int out_size) {
    (void)in_sizes; (void)n_in; (void)out_size;
    static EncodeFn enc = nullptr;
    static void* scratch = nullptr;
    if (!enc) {
        cudaFuncSetAttribute(fused_decode_kernel, cudaFuncAttributeMaxDynamicSharedMemorySize, (int)SMEM_BYTES);
        cudaGetSymbolAddress(&scratch, g_scratch);
        void* fn = nullptr;
        cudaDriverEntryPointQueryResult qr;
        cudaGetDriverEntryPoint("cuTensorMapEncodeTiled", &fn, cudaEnableDefault, &qr);
        enc = (EncodeFn)fn;
    }
    CUtensorMap map_wq, map_v, map_wo, map_wg, map_wu, map_wd;
    make_map(enc, &map_wq, d_in[3], 64, D_MODEL, NHEAD * 2, NHEAD * DH * 2, 128, 64, 128, 1);
    make_map(enc, &map_v, d_in[2], 64, 2ull * NHEAD * SK * 2, 1, 128, 128, 64, 128, 1);
    make_map(enc, &map_wo, d_in[4], 64, NHEAD * DH, D_MODEL / 64, D_MODEL * 2, 128, 64, 32, 4);
    make_map(enc, &map_wg, d_in[6], 32, D_MODEL, NUNIT, FF * 2, 64, 32, 256, 1);
    make_map(enc, &map_wu, d_in[7], 32, D_MODEL, NUNIT, FF * 2, 64, 32, 256, 1);
    make_map(enc, &map_wd, d_in[8], D_MODEL, 32, NUNIT, D_MODEL * 2, 32 * D_MODEL * 2, 32, 32, 8);
    typedef const __nv_bfloat16* P;
    fused_decode_kernel<<<NCTA, NTHREADS, SMEM_BYTES>>>((P)d_in[1], (P)d_in[0], (P)d_in[9], (__nv_bfloat16*)d_out, (Scratch*)scratch,
                                                        map_wq, map_v, map_wo, map_wg, map_wu, map_wd);
}
```
